```python
import torch

def _softmax(x, axis=-1):
    return torch.softmax(x, dim=axis)
def _gelu(x):
    return torch.nn.functional.gelu(x, approximate="tanh")
def _silu(x):
    return torch.nn.functional.silu(x)
def _sigmoid(x):
    return torch.sigmoid(x)
def _layernorm(x, axis=-1, eps=1e-5):
    m = x.mean(dim=axis, keepdim=True)
    v = x.var(dim=axis, keepdim=True, unbiased=False)
    return (x - m) / torch.sqrt(v + eps)
def _scatter_add(tgt, idx, src, axis=0):
    return tgt.clone().index_add_(axis, idx, src)
def _segment_sum(src, seg, n):
    out = torch.zeros((n,) + src.shape[1:], dtype=src.dtype)
    return out.index_add_(0, seg, src)
def _pad(x, pw):
    flat = tuple(v for pair in reversed(pw) for v in pair)
    return torch.nn.functional.pad(x, flat)

kernel_name = 'concat_heads__gqa_block_cached__sliding_block_cached__decode'

def setup_inputs():

    _w = (lambda a: (lambda t: t.to(torch.bfloat16) if t.is_floating_point() else t)(torch.as_tensor(a)))
    def _A_setup():
        B, Sq, D = 2, 1, 448
        Hq, Hkv, Sk, Dh = 16, 8, 8192, 256
        assert Hq % Hkv == 0, (Hq, Hkv)
        return {
            "x": _w((lambda *s: torch.randn(*s, dtype=torch.bfloat16) * 0.8)(B, Sq, D)),
            "k_cache": _w((lambda *s: torch.randn(*s, dtype=torch.bfloat16) * 1.6)(B, Hkv, Sk, Dh)),
            "v_cache": _w((lambda *s: torch.randn(*s, dtype=torch.bfloat16) * 0.2)(B, Hkv, Sk, Dh)),
            "wq": _w((lambda *s: torch.randn(*s, dtype=torch.bfloat16) * 1.6)(D, Hq * Dh) * (D ** -0.5)),
            "wo": _w((lambda *s: torch.randn(*s, dtype=torch.bfloat16) * 0.2)(Hq * Dh, D) * ((Hq * Dh) ** -0.5)),
        }
    _A_in = _A_setup()

    def _B_setup():
        B, Sq, D = 2, 1, 448
        Hq, Hkv, Sk, Dh = 16, 8, 8192, 256
        assert Hq % Hkv == 0, (Hq, Hkv)
        return {
            "x": _w((lambda *s: torch.randn(*s, dtype=torch.bfloat16) * 0.8)(B, Sq, D)),
            "k_cache": _w((lambda *s: torch.randn(*s, dtype=torch.bfloat16) * 1.6)(B, Hkv, Sk, Dh)),
            "v_cache": _w((lambda *s: torch.randn(*s, dtype=torch.bfloat16) * 0.2)(B, Hkv, Sk, Dh)),
            "wq": _w((lambda *s: torch.randn(*s, dtype=torch.bfloat16) * 1.6)(D, Hq * Dh) * (D ** -0.5)),
            "wo": _w((lambda *s: torch.randn(*s, dtype=torch.bfloat16) * 0.2)(Hq * Dh, D) * ((Hq * Dh) ** -0.5)),
        }
    _B_in = _B_setup()

    return {
        "A_x": _A_in["x"],
        "A_k_cache": _A_in["k_cache"],
        "A_v_cache": _A_in["v_cache"],
        "A_wq": _A_in["wq"],
        "A_wo": _A_in["wo"],
        "B_x": _B_in["x"],
        "B_k_cache": _B_in["k_cache"],
        "B_v_cache": _B_in["v_cache"],
        "B_wq": _B_in["wq"],
        "B_wo": _B_in["wo"],
    }

def reference(A_x, A_k_cache, A_v_cache, A_wq, A_wo, B_x, B_k_cache, B_v_cache, B_wq, B_wo):
    def _A_ref(x, k_cache, v_cache, wq, wo):
        B, Sq, D = x.shape
        Hq, Dh = 16, 256
        Hkv = k_cache.shape[1]
        rep = Hq // Hkv
        q = (lambda x, *d: x.permute(*d))((x @ wq).reshape(B, Sq, Hq, Dh), 0, 2, 1, 3)
        k = (lambda x, n, axis: torch.repeat_interleave(x, n, dim=axis))(k_cache, rep, axis=1)
        v = (lambda x, n, axis: torch.repeat_interleave(x, n, dim=axis))(v_cache, rep, axis=1)
        scores = torch.einsum("bhqd,bhkd->bhqk", q, k) * (Dh ** -0.5)
        p = _softmax(scores, axis=-1)
        o = torch.einsum("bhqk,bhkd->bhqd", p, v)
        return (lambda x, *d: x.permute(*d))(o, 0, 2, 1, 3).reshape(B, Sq, Hq * Dh) @ wo

    def _B_ref(x, k_cache, v_cache, wq, wo):
        B, Sq, D = x.shape
        Hq, Dh = 16, 256
        Hkv, Sk = k_cache.shape[1], k_cache.shape[2]
        W = min(4096, max(256, Sk // 4))
        rep = Hq // Hkv
        q = (lambda x, *d: x.permute(*d))((x @ wq).reshape(B, Sq, Hq, Dh), 0, 2, 1, 3)
        k = (lambda x, n, axis: torch.repeat_interleave(x, n, dim=axis))(k_cache[:, :, Sk - W:, :], rep, axis=1)
        v = (lambda x, n, axis: torch.repeat_interleave(x, n, dim=axis))(v_cache[:, :, Sk - W:, :], rep, axis=1)
        scores = torch.einsum("bhqd,bhkd->bhqk", q, k) * (Dh ** -0.5)
        p = _softmax(scores, axis=-1)
        o = torch.einsum("bhqk,bhkd->bhqd", p, v)
        return (lambda x, *d: x.permute(*d))(o, 0, 2, 1, 3).reshape(B, Sq, Hq * Dh) @ wo

    a = _A_ref(A_x, A_k_cache, A_v_cache, A_wq, A_wo)
    b = _B_ref(B_x, B_k_cache, B_v_cache, B_wq, B_wo)
    return torch.concatenate([a, b], axis=-1)
```

```cpp
#include <cuda_runtime.h>
#include <cuda.h>
#include <cuda_bf16.h>
#include <stdint.h>

namespace dk {

constexpr int NCTA     = 128;
constexpr int NTHREADS = 160;
constexpr int SLOT     = 32768;
constexpr int NT_B     = 4;
constexpr int NT_A     = 16;
constexpr int NITEMS   = 2 + 2 * (NT_A + NT_B) + 2;
constexpr int WQ_BYTES = 224 * 128;
constexpr int X_BYTES  = 2 * 448 * 2;
#define DK_STAGES 5
#define DK_RR 0
constexpr long long SPIN_LIMIT = 4000000000LL;

template <int S> struct Smem {
    static constexpr int ring = 0;
    static constexpr int red  = S * SLOT;
    static constexpr int ml   = red + 8192;
    static constexpr int xs   = ml + 64;
    static constexpr int qs   = xs + X_BYTES;
    static constexpr int qt   = qs + 2048;
    static constexpr int os   = qt + 256;
    static constexpr int bars = os + 256;
    static constexpr int total = bars + 16 * S + 1024;
};

struct Params {
    const __nv_bfloat16* xA;
    const __nv_bfloat16* xB;
    __nv_bfloat16* out;
};

__device__ unsigned g_epoch;
__device__ __align__(128) uint2 g_q[2][2][2048];
__device__ __align__(128) uint4 g_part[2][16][4][2][8][32];
__device__ __align__(128) uint4 g_out[2][224][64][2];

__device__ __forceinline__ uint32_t smem_u32(const void* p) { return (uint32_t)__cvta_generic_to_shared(p); }
__device__ __forceinline__ void mbar_init(uint32_t bar, uint32_t cnt) {
    asm volatile("mbarrier.init.shared::cta.b64 [%0], %1;" ::"r"(bar), "r"(cnt) : "memory");
}
__device__ __forceinline__ void mbar_expect_tx(uint32_t bar, uint32_t bytes) {
    asm volatile("mbarrier.arrive.expect_tx.shared::cta.b64 _, [%0], %1;" ::"r"(bar), "r"(bytes) : "memory");
}
__device__ __forceinline__ void mbar_arrive(uint32_t bar) {
    asm volatile("mbarrier.arrive.shared::cta.b64 _, [%0];" ::"r"(bar) : "memory");
}
__device__ __forceinline__ bool mbar_try(uint32_t bar, uint32_t parity) {
    uint32_t ok;
    asm volatile("{\n.reg .pred p;\nmbarrier.try_wait.parity.shared::cta.b64 p, [%1], %2;\nselp.u32 %0, 1, 0, p;\n}"
                 : "=r"(ok) : "r"(bar), "r"(parity) : "memory");
    return ok != 0;
}
__device__ __forceinline__ void mbar_wait(uint32_t bar, uint32_t parity) {
    if (mbar_try(bar, parity)) return;
    const long long t0 = clock64();
    while (!mbar_try(bar, parity))
        if (clock64() - t0 > SPIN_LIMIT) __trap();
}
__device__ __forceinline__ void cons_sync() { asm volatile("bar.sync 1, 128;" ::: "memory"); }

__device__ __forceinline__ void tma2d(uint32_t dst, const CUtensorMap* tm, int c0, int c1, uint32_t bar, uint64_t pol) {
    asm volatile("cp.async.bulk.tensor.2d.shared::cluster.global.mbarrier::complete_tx::bytes.L2::cache_hint [%0], [%1, {%3, %4}], [%2], %5;"
                 ::"r"(dst), "l"(tm), "r"(bar), "r"(c0), "r"(c1), "l"(pol) : "memory");
}
__device__ __forceinline__ void tma3d(uint32_t dst, const CUtensorMap* tm, int c0, int c1, int c2, uint32_t bar, uint64_t pol) {
    asm volatile("cp.async.bulk.tensor.3d.shared::cluster.global.mbarrier::complete_tx::bytes.L2::cache_hint [%0], [%1, {%3, %4, %5}], [%2], %6;"
                 ::"r"(dst), "l"(tm), "r"(bar), "r"(c0), "r"(c1), "r"(c2), "l"(pol) : "memory");
}
__device__ __forceinline__ void bulk1d(uint32_t dst, const void* src, uint32_t bytes, uint32_t bar) {
    asm volatile("cp.async.bulk.shared::cluster.global.mbarrier::complete_tx::bytes [%0], [%1], %2, [%3];"
                 ::"r"(dst), "l"(src), "r"(bytes), "r"(bar) : "memory");
}
__device__ __forceinline__ void prefetch_map(const CUtensorMap* tm) {
    asm volatile("prefetch.tensormap [%0];" ::"l"(tm) : "memory");
}

__device__ __forceinline__ void ldsm4(uint32_t (&r)[4], uint32_t addr) {
    asm volatile("ldmatrix.sync.aligned.m8n8.x4.shared.b16 {%0,%1,%2,%3}, [%4];"
                 : "=r"(r[0]), "=r"(r[1]), "=r"(r[2]), "=r"(r[3]) : "r"(addr) : "memory");
}
__device__ __forceinline__ void ldsm4t(uint32_t (&r)[4], uint32_t addr) {
    asm volatile("ldmatrix.sync.aligned.m8n8.x4.trans.shared.b16 {%0,%1,%2,%3}, [%4];"
                 : "=r"(r[0]), "=r"(r[1]), "=r"(r[2]), "=r"(r[3]) : "r"(addr) : "memory");
}
__device__ __forceinline__ void mma16816(float (&c)[4], const uint32_t (&a)[4], uint32_t b0, uint32_t b1) {
    asm volatile("mma.sync.aligned.m16n8k16.row.col.f32.bf16.bf16.f32 {%0,%1,%2,%3}, {%4,%5,%6,%7}, {%8,%9}, {%0,%1,%2,%3};"
                 : "+f"(c[0]), "+f"(c[1]), "+f"(c[2]), "+f"(c[3])
                 : "r"(a[0]), "r"(a[1]), "r"(a[2]), "r"(a[3]), "r"(b0), "r"(b1));
}
__device__ __forceinline__ uint32_t movmat(uint32_t a) {
    uint32_t d;
    asm volatile("movmatrix.sync.aligned.m8n8.trans.b16 %0, %1;" : "=r"(d) : "r"(a));
    return d;
}
__device__ __forceinline__ uint32_t pack_bf16(float lo, float hi) {
    uint32_t d;
    asm("cvt.rn.bf16x2.f32 %0, %1, %2;" : "=r"(d) : "f"(hi), "f"(lo));
    return d;
}
__device__ __forceinline__ float ex2(float x) {
    float y;
    asm("ex2.approx.ftz.f32 %0, %1;" : "=f"(y) : "f"(x));
    return y;
}
__device__ __forceinline__ uint32_t lds32(uint32_t addr) {
    uint32_t v;
    asm volatile("ld.shared.u32 %0, [%1];" : "=r"(v) : "r"(addr) : "memory");
    return v;
}

__device__ __forceinline__ void st_ll8(void* p, uint32_t a, uint32_t tag) {
    asm volatile("{\n.reg .b64 v;\nmov.b64 v, {%1, %2};\nst.relaxed.gpu.global.b64 [%0], v;\n}" ::"l"(p), "r"(a), "r"(tag) : "memory");
}
__device__ __forceinline__ void st_ll16(void* p, uint32_t a, uint32_t b, uint32_t c, uint32_t d) {
    asm volatile("{\n.reg .b128 v;\nmov.b128 v, {%1, %2, %3, %4};\nst.relaxed.gpu.global.b128 [%0], v;\n}"
                 ::"l"(p), "r"(a), "r"(b), "r"(c), "r"(d) : "memory");
}
__device__ __forceinline__ uint4 ld_ll16(const void* p) {
    uint4 r;
    asm volatile("{\n.reg .b128 v;\nld.relaxed.gpu.global.b128 v, [%4];\nmov.b128 {%0, %1, %2, %3}, v;\n}"
                 : "=r"(r.x), "=r"(r.y), "=r"(r.z), "=r"(r.w) : "l"(p) : "memory");
    return r;
}
__device__ __forceinline__ uint4 ld_ll8x2(const void* p) {
    unsigned long long a, b;
    asm volatile("ld.relaxed.gpu.global.v2.b64 {%0, %1}, [%2];" : "=l"(a), "=l"(b) : "l"(p) : "memory");
    return make_uint4((uint32_t)a, (uint32_t)(a >> 32), (uint32_t)b, (uint32_t)(b >> 32));
}

#define TSTAMP(i)

template <int S>
__global__ void __launch_bounds__(NTHREADS, 1)
decode_kernel(const __grid_constant__ CUtensorMap tmKA, const __grid_constant__ CUtensorMap tmVA,
              const __grid_constant__ CUtensorMap tmKB, const __grid_constant__ CUtensorMap tmVB,
              const __grid_constant__ CUtensorMap tmWqA, const __grid_constant__ CUtensorMap tmWqB,
              const __grid_constant__ CUtensorMap tmWoA, const __grid_constant__ CUtensorMap tmWoB,
              const Params prm)
{
    using L = Smem<S>;
    extern __shared__ char smem_raw[];
    const uint32_t base = (smem_u32(smem_raw) + 1023u) & ~1023u;
    char* sm = smem_raw + (base - smem_u32(smem_raw));
    const uint32_t fullb = base + L::bars, emptyb = fullb + 8 * S;

    const int tid = threadIdx.x, warp = tid >> 5, lane = tid & 31;
    const int j = blockIdx.x;
    const int grp = j >> 3, r = j & 7;
    const int pj = j >> 6, sj = j & 63;

    TSTAMP(0);
    const CUtensorMap* tmWq = pj ? &tmWqB : &tmWqA;
    const CUtensorMap* tmWo = pj ? &tmWoB : &tmWoA;
    uint64_t pol = 0;
    auto issue = [&](int i, int slot) {
        const uint32_t bar = fullb + 8 * slot, dst = base + L::ring + slot * SLOT;
        if (i < 2) {
            mbar_expect_tx(bar, WQ_BYTES + (i == 0 ? X_BYTES : 0));
            tma2d(dst, tmWq, sj * 64, i * 224, bar, pol);
            if (i == 0) bulk1d(base + L::xs, pj ? prm.xB : prm.xA, X_BYTES, bar);
        } else if (i < NITEMS - 2) {
            const int k = i - 2, t = k >> 1, isV = k & 1;
            int row; const CUtensorMap* tm;
            if (t < NT_B) {
                row = grp * 8192 + 6144 + (DK_RR ? (t * 8 + r) * 64 : (r * NT_B + t) * 64);
                tm = isV ? &tmVB : &tmKB;
            } else {
                const int ta = t - NT_B;
                row = grp * 8192 + (DK_RR ? (ta * 8 + r) * 64 : (r * NT_A + ta) * 64);
                tm = isV ? &tmVA : &tmKA;
            }
            mbar_expect_tx(bar, SLOT);
            tma3d(dst, tm, 0, row, 0, bar, pol);
        } else {
            mbar_expect_tx(bar, SLOT);
            tma3d(dst, tmWo, 0, sj * 64, (i - (NITEMS - 2)) * 4, bar, pol);
        }
    };
    uint32_t tag = 0;
    if (warp == 4) {
        if (lane == 0) {
            prefetch_map(tmWq);
            for (int s = 0; s < S; s++) { mbar_init(fullb + 8 * s, 1); mbar_init(emptyb + 8 * s, 4); }
            asm volatile("fence.mbarrier_init.release.cluster;" ::: "memory");
            asm volatile("fence.proxy.async;" ::: "memory");
            asm volatile("createpolicy.fractional.L2::evict_first.b64 %0, 1.0;" : "=l"(pol));
            #pragma unroll 1
            for (int i = 0; i < S; i++) {
                issue(i, i);
                if (i == 1) { prefetch_map(&tmKB); prefetch_map(&tmVB); }
            }
            prefetch_map(&tmKA); prefetch_map(&tmVA); prefetch_map(tmWo);
        }
    } else if (warp < 4) {
        asm volatile("ld.relaxed.gpu.global.u32 %0, [%1];" : "=r"(tag) : "l"(&g_epoch) : "memory");
        tag += 1;
    }
    __syncthreads();

    if (warp == 4) {
        if (lane == 0) {
            int slot = 0; uint32_t ph = 0;
            #pragma unroll 1
            for (int i = S; i < NITEMS; i++) {
                mbar_wait(emptyb + 8 * slot, ph);
                issue(i, slot);
                if (++slot == S) { slot = 0; ph ^= 1; }
            }
        }
        return;
    }

    const int g = lane >> 2, t4 = lane & 3;
    int slot = 0; uint32_t ph = 0;
    auto advance = [&]() { if (++slot == S) { slot = 0; ph ^= 1; } };
    auto release = [&]() { __syncwarp(); if (lane == 0) mbar_arrive(emptyb + 8 * slot); };

    const uint32_t l7 = lane & 7;
    const uint32_t offT = (l7 + (lane >> 4) * 8) * 128 + ((((lane >> 3) & 1) ^ l7) << 4);
    const uint32_t offP = (l7 + ((lane >> 3) & 1) * 8) * 128 + (((lane >> 4) ^ l7) << 4);

    {
        float c0[4] = {0.f, 0.f, 0.f, 0.f}, c1[4] = {0.f, 0.f, 0.f, 0.f};
        const uint32_t xa = base + L::xs + (g & 1) * 896 + t4 * 4;
        #pragma unroll
        for (int h = 0; h < 2; h++) {
            mbar_wait(fullb + 8 * slot, ph);
            const uint32_t tb = base + L::ring + slot * SLOT + (offT ^ (warp << 5));
            #pragma unroll
            for (int ks = 0; ks < 14; ks++) {
                uint32_t a[4];
                ldsm4t(a, tb + ks * 2048);
                uint32_t b0 = lds32(xa + (h * 14 + ks) * 32), b1 = lds32(xa + (h * 14 + ks) * 32 + 16);
                if (g >= 2) { b0 = 0; b1 = 0; }
                if (ks & 1) mma16816(c1, a, b0, b1); else mma16816(c0, a, b0, b1);
            }
            release();
            advance();
        }
        TSTAMP(1);
        __nv_bfloat16* qt = reinterpret_cast<__nv_bfloat16*>(sm + L::qt);
        if (t4 == 0) {
            qt[warp * 16 + g]          = __float2bfloat16_rn(c0[0] + c1[0]);
            qt[64 + warp * 16 + g]     = __float2bfloat16_rn(c0[1] + c1[1]);
            qt[warp * 16 + g + 8]      = __float2bfloat16_rn(c0[2] + c1[2]);
            qt[64 + warp * 16 + g + 8] = __float2bfloat16_rn(c0[3] + c1[3]);
        }
        __syncwarp();
        if (lane < 16) {
            const int b = lane >> 3, i = lane & 7;
            const uint32_t v = *reinterpret_cast<const uint32_t*>(qt + b * 64 + warp * 16 + i * 2);
            st_ll8(&g_q[pj][b][sj * 32 + warp * 8 + i], v, tag);
        }
    }
    const int bq = grp >> 3, hkv = grp & 7;
    {
        const uint2* s0 = &g_q[0][bq][hkv * 256 + tid * 2];
        const uint2* s1 = &g_q[1][bq][hkv * 256 + tid * 2];
        uint4 v0, v1;
        const long long t0 = clock64();
        while (true) {
            v0 = ld_ll8x2(s0);
            v1 = ld_ll8x2(s1);
            if (__all_sync(0xffffffffu, v0.y == tag && v0.w == tag && v1.y == tag && v1.w == tag)) break;
            if (clock64() - t0 > SPIN_LIMIT) __trap();
        }
        uint2* qs = reinterpret_cast<uint2*>(sm + L::qs);
        qs[tid] = make_uint2(v0.x, v0.z);
        qs[128 + tid] = make_uint2(v1.x, v1.z);
        cons_sync();
    }
    TSTAMP(2);

    constexpr float CS = 1.4426950408889634f / 16.0f;
    #pragma unroll 1
    for (int pi = 0; pi < 2; pi++) {
        const int p = 1 - pi;
        const int ntiles = p ? NT_B : NT_A;
        uint32_t qf[16][2];
        {
            const uint32_t qa = base + L::qs + p * 1024 + (g & 1) * 512 + t4 * 4;
            #pragma unroll
            for (int ks = 0; ks < 16; ks++) {
                qf[ks][0] = lds32(qa + ks * 32);
                qf[ks][1] = lds32(qa + ks * 32 + 16);
                if (g >= 2) { qf[ks][0] = 0; qf[ks][1] = 0; }
            }
        }
        float o[16][4];
        #pragma unroll
        for (int i = 0; i < 16; i++) { o[i][0] = 0.f; o[i][1] = 0.f; o[i][2] = 0.f; o[i][3] = 0.f; }
        float m0 = -INFINITY, m1 = -INFINITY, l0 = 0.f, l1 = 0.f;

        #pragma unroll 1
        for (int t = 0; t < ntiles; t++) {
            mbar_wait(fullb + 8 * slot, ph);
            float sa[4] = {0.f, 0.f, 0.f, 0.f}, sb[4] = {0.f, 0.f, 0.f, 0.f};
            {
                const uint32_t kb = base + L::ring + slot * SLOT + warp * 2048;
                #pragma unroll
                for (int ks = 0; ks < 16; ks++) {
                    uint32_t a[4];
                    ldsm4(a, kb + (ks >> 2) * 8192 + (offP ^ ((ks & 3) << 5)));
                    if (ks & 1) mma16816(sb, a, qf[ks][0], qf[ks][1]); else mma16816(sa, a, qf[ks][0], qf[ks][1]);
                }
            }
            release();
            advance();
            const float s0 = sa[0] + sb[0], s1 = sa[1] + sb[1], s2 = sa[2] + sb[2], s3 = sa[3] + sb[3];
            float x0 = fmaxf(s0, s2), x1 = fmaxf(s1, s3);
            #pragma unroll
            for (int d = 4; d < 32; d <<= 1) {
                x0 = fmaxf(x0, __shfl_xor_sync(0xffffffffu, x0, d));
                x1 = fmaxf(x1, __shfl_xor_sync(0xffffffffu, x1, d));
            }
            if (__any_sync(0xffffffffu, x0 > m0 || x1 > m1)) {
                const float n0 = fmaxf(m0, x0), n1 = fmaxf(m1, x1);
                const float f0 = ex2((m0 - n0) * CS), f1 = ex2((m1 - n1) * CS);
                m0 = n0; m1 = n1;
                l0 *= f0; l1 *= f1;
                #pragma unroll
                for (int i = 0; i < 16; i++) { o[i][0] *= f0; o[i][1] *= f1; o[i][2] *= f0; o[i][3] *= f1; }
            }
            const float mc0 = m0 * CS, mc1 = m1 * CS;
            const float p0 = ex2(fmaf(s0, CS, -mc0)), p1 = ex2(fmaf(s1, CS, -mc1));
            const float p2 = ex2(fmaf(s2, CS, -mc0)), p3 = ex2(fmaf(s3, CS, -mc1));
            l0 += p0 + p2; l1 += p1 + p3;
            const uint32_t pb0 = movmat(pack_bf16(p0, p1)), pb1 = movmat(pack_bf16(p2, p3));
            mbar_wait(fullb + 8 * slot, ph);
            {
                const uint32_t vb = base + L::ring + slot * SLOT + warp * 2048;
                #pragma unroll
                for (int mt = 0; mt < 16; mt++) {
                    uint32_t a[4];
                    ldsm4t(a, vb + (mt >> 2) * 8192 + (offT ^ ((mt & 3) << 5)));
                    mma16816(o[mt], a, pb0, pb1);
                }
            }
            release();
            advance();
            if (pi == 0 && t == 0) TSTAMP(3);
        }
        TSTAMP(pi == 0 ? 4 : 6);

        #pragma unroll
        for (int d = 4; d < 32; d <<= 1) {
            l0 += __shfl_xor_sync(0xffffffffu, l0, d);
            l1 += __shfl_xor_sync(0xffffffffu, l1, d);
        }
        float* red = reinterpret_cast<float*>(sm + L::red);
        float4* ml = reinterpret_cast<float4*>(sm + L::ml);
        if (pi == 1) cons_sync();
        if (t4 == 0) {
            float2* rw = reinterpret_cast<float2*>(red) + warp * 256 + g;
            #pragma unroll
            for (int mt = 0; mt < 16; mt++) {
                rw[mt * 16]     = make_float2(o[mt][0], o[mt][1]);
                rw[mt * 16 + 8] = make_float2(o[mt][2], o[mt][3]);
            }
            if (g == 0) ml[warp] = make_float4(m0 * CS, m1 * CS, l0, l1);
        }
        cons_sync();
        {
            const float4 w0 = ml[0], w1 = ml[1], w2 = ml[2], w3 = ml[3];
            const float M0 = fmaxf(fmaxf(w0.x, w1.x), fmaxf(w2.x, w3.x));
            const float M1 = fmaxf(fmaxf(w0.y, w1.y), fmaxf(w2.y, w3.y));
            const float e00 = ex2(w0.x - M0), e01 = ex2(w1.x - M0), e02 = ex2(w2.x - M0), e03 = ex2(w3.x - M0);
            const float e10 = ex2(w0.y - M1), e11 = ex2(w1.y - M1), e12 = ex2(w2.y - M1), e13 = ex2(w3.y - M1);
            const float L0 = e00 * w0.z + e01 * w1.z + e02 * w2.z + e03 * w3.z;
            const float L1 = e10 * w0.w + e11 * w1.w + e12 * w2.w + e13 * w3.w;
            const float i0 = 1.0f / L0, i1 = 1.0f / L1;
            const float lse0 = M0 + log2f(L0), lse1 = M1 + log2f(L1);
            const float4* r4 = reinterpret_cast<const float4*>(red) + tid;
            const float4 a0 = r4[0], a1 = r4[128], a2 = r4[256], a3 = r4[384];
            const float h0a = (e00 * a0.x + e01 * a1.x + e02 * a2.x + e03 * a3.x) * i0;
            const float h1a = (e10 * a0.y + e11 * a1.y + e12 * a2.y + e13 * a3.y) * i1;
            const float h0b = (e00 * a0.z + e01 * a1.z + e02 * a2.z + e03 * a3.z) * i0;
            const float h1b = (e10 * a0.w + e11 * a1.w + e12 * a2.w + e13 * a3.w) * i1;
            st_ll16(&g_part[p][hkv * 2][warp][bq][r][lane], __float_as_uint(h0a), __float_as_uint(h0b), __float_as_uint(lse0), tag);
            st_ll16(&g_part[p][hkv * 2 + 1][warp][bq][r][lane], __float_as_uint(h1a), __float_as_uint(h1b), __float_as_uint(lse1), tag);
        }
        TSTAMP(pi == 0 ? 5 : 7);
    }

    if (warp < 2) {
        const uint4* src = &g_part[pj][sj >> 2][sj & 3][warp][0][lane];
        uint4 v[8];
        const long long t0 = clock64();
        while (true) {
            bool ok = true;
            #pragma unroll
            for (int i = 0; i < 8; i++) v[i] = ld_ll16(src + i * 32);
            #pragma unroll
            for (int i = 0; i < 8; i++) ok = ok && (v[i].w == tag);
            if (__all_sync(0xffffffffu, ok)) break;
            if (clock64() - t0 > SPIN_LIMIT) __trap();
        }
        float M = __uint_as_float(v[0].z);
        #pragma unroll
        for (int i = 1; i < 8; i++) M = fmaxf(M, __uint_as_float(v[i].z));
        float ws = 0.f, oa = 0.f, ob = 0.f;
        #pragma unroll
        for (int i = 0; i < 8; i++) {
            const float w = ex2(__uint_as_float(v[i].z) - M);
            ws += w;
            oa = fmaf(w, __uint_as_float(v[i].x), oa);
            ob = fmaf(w, __uint_as_float(v[i].y), ob);
        }
        const float inv = 1.0f / ws;
        reinterpret_cast<uint32_t*>(sm + L::os)[warp * 32 + lane] = pack_bf16(oa * inv, ob * inv);
    }
    cons_sync();
    TSTAMP(8);

    {
        uint32_t of[4][2];
        const uint32_t oa = base + L::os + (g & 1) * 128 + t4 * 4;
        #pragma unroll
        for (int ks = 0; ks < 4; ks++) {
            of[ks][0] = lds32(oa + ks * 32);
            of[ks][1] = lds32(oa + ks * 32 + 16);
            if (g >= 2) { of[ks][0] = 0; of[ks][1] = 0; }
        }
        #pragma unroll
        for (int h = 0; h < 2; h++) {
            mbar_wait(fullb + 8 * slot, ph);
            if (h == 1) TSTAMP(9);
            const uint32_t wb = base + L::ring + slot * SLOT + (offT ^ (warp << 5));
            constexpr int NC[2] = {4, 3};
            float acc[4][4];
            #pragma unroll
            for (int c = 0; c < NC[h]; c++) {
                acc[c][0] = 0.f; acc[c][1] = 0.f; acc[c][2] = 0.f; acc[c][3] = 0.f;
                #pragma unroll
                for (int ks = 0; ks < 4; ks++) {
                    uint32_t a[4];
                    ldsm4t(a, wb + c * 8192 + ks * 2048);
                    mma16816(acc[c], a, of[ks][0], of[ks][1]);
                }
            }
            if (t4 == 0) {
                #pragma unroll
                for (int c = 0; c < NC[h]; c++) {
                    const int col = (h * 4 + c) * 64 + warp * 16 + g;
                    st_ll16(&g_out[pj][col >> 1][sj][g & 1], __float_as_uint(acc[c][0]), __float_as_uint(acc[c][1]), tag, 0u);
                    st_ll16(&g_out[pj][(col + 8) >> 1][sj][g & 1], __float_as_uint(acc[c][2]), __float_as_uint(acc[c][3]), tag, 0u);
                }
            }
            advance();
        }
    }
    TSTAMP(10);

    const int W = j * 4 + warp;
    if (W < 448) {
        const int pf = W / 224, cp = W - pf * 224;
        const uint4* src = &g_out[pf][cp][0][0] + lane;
        uint4 v[4];
        const long long t0 = clock64();
        while (true) {
            #pragma unroll
            for (int i = 0; i < 4; i++) v[i] = ld_ll16(src + i * 32);
            if (__all_sync(0xffffffffu, v[0].z == tag && v[1].z == tag && v[2].z == tag && v[3].z == tag)) break;
            if (clock64() - t0 > SPIN_LIMIT) __trap();
        }
        float a = (__uint_as_float(v[0].x) + __uint_as_float(v[1].x)) + (__uint_as_float(v[2].x) + __uint_as_float(v[3].x));
        float b = (__uint_as_float(v[0].y) + __uint_as_float(v[1].y)) + (__uint_as_float(v[2].y) + __uint_as_float(v[3].y));
        #pragma unroll
        for (int d = 2; d < 32; d <<= 1) {
            a += __shfl_xor_sync(0xffffffffu, a, d);
            b += __shfl_xor_sync(0xffffffffu, b, d);
        }
        const float a1 = __shfl_xor_sync(0xffffffffu, a, 1), b1 = __shfl_xor_sync(0xffffffffu, b, 1);
        if (lane == 0) *reinterpret_cast<uint32_t*>(prm.out + pf * 448 + cp * 2) = pack_bf16(a, a1);
        if (lane == 1) *reinterpret_cast<uint32_t*>(prm.out + 896 + pf * 448 + cp * 2) = pack_bf16(b1, b);
        if (W == 0 && lane == 0)
            asm volatile("st.relaxed.gpu.global.u32 [%0], %1;" ::"l"(&g_epoch), "r"(tag) : "memory");
    }
    TSTAMP(11);
}

typedef CUresult (*EncodeFn)(CUtensorMap*, CUtensorMapDataType, cuuint32_t, void*, const cuuint64_t*, const cuuint64_t*,
                             const cuuint32_t*, const cuuint32_t*, CUtensorMapInterleave, CUtensorMapSwizzle,
                             CUtensorMapL2promotion, CUtensorMapFloatOOBfill);

inline CUtensorMap make_map(EncodeFn enc, const void* ptr, int rank, const cuuint64_t* dims, const cuuint64_t* strides, const cuuint32_t* box) {
    CUtensorMap m;
    const cuuint32_t es[3] = {1, 1, 1};
    enc(&m, CU_TENSOR_MAP_DATA_TYPE_BFLOAT16, rank, const_cast<void*>(ptr), dims, strides, box, es,
        CU_TENSOR_MAP_INTERLEAVE_NONE, CU_TENSOR_MAP_SWIZZLE_128B, CU_TENSOR_MAP_L2_PROMOTION_NONE,
        CU_TENSOR_MAP_FLOAT_OOB_FILL_NONE);
    return m;
}

}

extern "C" void kernel_launch(void* const* d_in, const int* in_sizes, int n_in, void* d_out, int out_size) {
    using namespace dk;
    (void)in_sizes; (void)n_in; (void)out_size;
    void* fn = nullptr;
    cudaDriverEntryPointQueryResult qr;
    cudaGetDriverEntryPoint("cuTensorMapEncodeTiled", &fn, cudaEnableDefault, &qr);
    EncodeFn enc = (EncodeFn)fn;

    const cuuint64_t kvd[3] = {64, 131072, 4}, kvs[2] = {512, 128};
    const cuuint32_t kvb[3] = {64, 64, 4};
    const cuuint64_t wqd[2] = {4096, 448}, wqs[1] = {8192};
    const cuuint32_t wqb[2] = {64, 224};
    const cuuint64_t wod[3] = {64, 4096, 7}, wos[2] = {896, 128};
    const cuuint32_t wob[3] = {64, 64, 4};
    const CUtensorMap kA = make_map(enc, d_in[1], 3, kvd, kvs, kvb), vA = make_map(enc, d_in[2], 3, kvd, kvs, kvb);
    const CUtensorMap kB = make_map(enc, d_in[6], 3, kvd, kvs, kvb), vB = make_map(enc, d_in[7], 3, kvd, kvs, kvb);
    const CUtensorMap wqA = make_map(enc, d_in[3], 2, wqd, wqs, wqb), wqB = make_map(enc, d_in[8], 2, wqd, wqs, wqb);
    const CUtensorMap woA = make_map(enc, d_in[4], 3, wod, wos, wob), woB = make_map(enc, d_in[9], 3, wod, wos, wob);
    Params prm;
    prm.xA = (const __nv_bfloat16*)d_in[0];
    prm.xB = (const __nv_bfloat16*)d_in[5];
    prm.out = (__nv_bfloat16*)d_out;

    constexpr int S = DK_STAGES;
    cudaFuncSetAttribute(decode_kernel<S>, cudaFuncAttributeMaxDynamicSharedMemorySize, Smem<S>::total);
    decode_kernel<S><<<NCTA, NTHREADS, Smem<S>::total>>>(kA, vA, kB, vB, wqA, wqB, woA, woB, prm);
}
```

```cpp
#include <cuda_runtime.h>
#include <cuda.h>
#include <cuda_bf16.h>
#include <stdint.h>

namespace dk {

constexpr int NCTA     = 128;
constexpr int NTHREADS = 192;
constexpr int SLOT     = 32768;
constexpr int NT_B     = 4;
constexpr int NT_A     = 16;
constexpr int NITEMS   = 2 + 2 * (NT_A + NT_B) + 2;
constexpr int WQ_BYTES = 224 * 128;
constexpr int X_BYTES  = 2 * 448 * 2;
#define DK_STAGES 6
#define DK_WIN 4
#define DK_WIN0 3
#define DK_N0 6
#define DK_PRETOUCH 1
#define DK_PREFETCH 9
#define DK_WWO 2
#define DK_CX 41
#define DK_CT 96
#define DK_CSLEEP 100
#define DK_NE 0
#define DK_WE DK_WIN
#define DK_PRED 1
#define DK_RA0 0
#define DK_RA1 0
#define DK_RAD 4
#define DK_RR 0
constexpr long long SPIN_LIMIT = 4000000000LL;

template <int S> struct Smem {
    static constexpr int ring = 0;
    static constexpr int red  = S * SLOT;
    static constexpr int ml   = red + 10240;
    static constexpr int xs   = ml + 128;
    static constexpr int qs   = xs + X_BYTES;
    static constexpr int os   = qs + 2048;
    static constexpr int bars = os + 256;
    static constexpr int total = bars + 16 * S + 1024;
};

struct Params {
    const __nv_bfloat16* xA;
    const __nv_bfloat16* xB;
    const __nv_bfloat16* wqA;
    const __nv_bfloat16* wqB;
    const __nv_bfloat16* kB;
    const __nv_bfloat16* vB;
    const __nv_bfloat16* kA;
    const __nv_bfloat16* vA;
    __nv_bfloat16* out;
    unsigned* epoch;
    uint2* q;
    uint4* part;
    uint4* outp;
};

__device__ __align__(128) unsigned g_epoch[64];
__device__ __align__(128) uint2 g_q[2][2][2048];
__device__ __align__(128) uint4 g_part[2][16][4][2][8][32];
__device__ __align__(128) uint4 g_out[2][56][64][8];

__device__ __forceinline__ uint32_t smem_u32(const void* p) { return (uint32_t)__cvta_generic_to_shared(p); }
__device__ __forceinline__ void mbar_init(uint32_t bar, uint32_t cnt) {
    asm volatile("mbarrier.init.shared::cta.b64 [%0], %1;" ::"r"(bar), "r"(cnt) : "memory");
}
__device__ __forceinline__ void mbar_expect_tx(uint32_t bar, uint32_t bytes) {
    asm volatile("mbarrier.arrive.expect_tx.shared::cta.b64 _, [%0], %1;" ::"r"(bar), "r"(bytes) : "memory");
}
__device__ __forceinline__ void mbar_arrive(uint32_t bar) {
    asm volatile("mbarrier.arrive.shared::cta.b64 _, [%0];" ::"r"(bar) : "memory");
}
__device__ __forceinline__ bool mbar_try(uint32_t bar, uint32_t parity) {
    uint32_t ok;
    asm volatile("{\n.reg .pred p;\nmbarrier.try_wait.parity.shared::cta.b64 p, [%1], %2;\nselp.u32 %0, 1, 0, p;\n}"
                 : "=r"(ok) : "r"(bar), "r"(parity) : "memory");
    return ok != 0;
}
__device__ __forceinline__ void mbar_wait(uint32_t bar, uint32_t parity) {
    if (mbar_try(bar, parity)) return;
    const long long t0 = clock64();
    while (!mbar_try(bar, parity))
        if (clock64() - t0 > SPIN_LIMIT) __trap();
}
template <typename T> __device__ __forceinline__ void pin(T*& p) { asm volatile("" : "+l"(p)); }
constexpr uint32_t POLL_LIMIT = 1u << 24;
__device__ __forceinline__ void cons_sync() { asm volatile("bar.sync 1, 128;" ::: "memory"); }

__device__ __forceinline__ void tma2d(uint32_t dst, const CUtensorMap* tm, int c0, int c1, uint32_t bar, uint64_t pol) {
    asm volatile("cp.async.bulk.tensor.2d.shared::cluster.global.mbarrier::complete_tx::bytes.L2::cache_hint [%0], [%1, {%3, %4}], [%2], %5;"
                 ::"r"(dst), "l"(tm), "r"(bar), "r"(c0), "r"(c1), "l"(pol) : "memory");
}
__device__ __forceinline__ void tma3d(uint32_t dst, const CUtensorMap* tm, int c0, int c1, int c2, uint32_t bar, uint64_t pol) {
    asm volatile("cp.async.bulk.tensor.3d.shared::cluster.global.mbarrier::complete_tx::bytes.L2::cache_hint [%0], [%1, {%3, %4, %5}], [%2], %6;"
                 ::"r"(dst), "l"(tm), "r"(bar), "r"(c0), "r"(c1), "r"(c2), "l"(pol) : "memory");
}
__device__ __forceinline__ void bulk1d(uint32_t dst, const void* src, uint32_t bytes, uint32_t bar) {
    asm volatile("cp.async.bulk.shared::cluster.global.mbarrier::complete_tx::bytes [%0], [%1], %2, [%3];"
                 ::"r"(dst), "l"(src), "r"(bytes), "r"(bar) : "memory");
}
__device__ __forceinline__ void prefetch_map(const CUtensorMap* tm) {
    asm volatile("prefetch.tensormap [%0];" ::"l"(tm) : "memory");
}

__device__ __forceinline__ void ldsm4(uint32_t (&r)[4], uint32_t addr) {
    asm volatile("ldmatrix.sync.aligned.m8n8.x4.shared.b16 {%0,%1,%2,%3}, [%4];"
                 : "=r"(r[0]), "=r"(r[1]), "=r"(r[2]), "=r"(r[3]) : "r"(addr) : "memory");
}
__device__ __forceinline__ void ldsm4t(uint32_t (&r)[4], uint32_t addr) {
    asm volatile("ldmatrix.sync.aligned.m8n8.x4.trans.shared.b16 {%0,%1,%2,%3}, [%4];"
                 : "=r"(r[0]), "=r"(r[1]), "=r"(r[2]), "=r"(r[3]) : "r"(addr) : "memory");
}
__device__ __forceinline__ void mma16816(float (&c)[4], const uint32_t (&a)[4], uint32_t b0, uint32_t b1) {
    asm volatile("mma.sync.aligned.m16n8k16.row.col.f32.bf16.bf16.f32 {%0,%1,%2,%3}, {%4,%5,%6,%7}, {%8,%9}, {%0,%1,%2,%3};"
                 : "+f"(c[0]), "+f"(c[1]), "+f"(c[2]), "+f"(c[3])
                 : "r"(a[0]), "r"(a[1]), "r"(a[2]), "r"(a[3]), "r"(b0), "r"(b1));
}
__device__ __forceinline__ uint32_t movmat(uint32_t a) {
    uint32_t d;
    asm volatile("movmatrix.sync.aligned.m8n8.trans.b16 %0, %1;" : "=r"(d) : "r"(a));
    return d;
}
__device__ __forceinline__ uint32_t pack_bf16(float lo, float hi) {
    uint32_t d;
    asm("cvt.rn.bf16x2.f32 %0, %1, %2;" : "=r"(d) : "f"(hi), "f"(lo));
    return d;
}
__device__ __forceinline__ float ex2(float x) {
    float y;
    asm("ex2.approx.ftz.f32 %0, %1;" : "=f"(y) : "f"(x));
    return y;
}
__device__ __forceinline__ float rcp(float x) {
    float y;
    asm("rcp.approx.ftz.f32 %0, %1;" : "=f"(y) : "f"(x));
    return y;
}
__device__ __forceinline__ float lg2(float x) {
    float y;
    asm("lg2.approx.ftz.f32 %0, %1;" : "=f"(y) : "f"(x));
    return y;
}
__device__ __forceinline__ uint32_t lds32(uint32_t addr) {
    uint32_t v;
    asm volatile("ld.shared.u32 %0, [%1];" : "=r"(v) : "r"(addr) : "memory");
    return v;
}

__device__ __forceinline__ void st_ll8(void* p, uint32_t a, uint32_t tag) {
    asm volatile("{\n.reg .b64 v;\nmov.b64 v, {%1, %2};\nst.relaxed.gpu.global.b64 [%0], v;\n}" ::"l"(p), "r"(a), "r"(tag) : "memory");
}
__device__ __forceinline__ void st_ll16(void* p, uint32_t a, uint32_t b, uint32_t c, uint32_t d) {
    asm volatile("{\n.reg .b128 v;\nmov.b128 v, {%1, %2, %3, %4};\nst.relaxed.gpu.global.b128 [%0], v;\n}"
                 ::"l"(p), "r"(a), "r"(b), "r"(c), "r"(d) : "memory");
}
__device__ __forceinline__ uint4 ld_ll16(const void* p) {
    uint4 r;
    asm volatile("{\n.reg .b128 v;\nld.relaxed.gpu.global.b128 v, [%4];\nmov.b128 {%0, %1, %2, %3}, v;\n}"
                 : "=r"(r.x), "=r"(r.y), "=r"(r.z), "=r"(r.w) : "l"(p) : "memory");
    return r;
}
__device__ __forceinline__ uint4 ld_ll8x2(const void* p) {
    unsigned long long a, b;
    asm volatile("ld.relaxed.gpu.global.v2.b64 {%0, %1}, [%2];" : "=l"(a), "=l"(b) : "l"(p) : "memory");
    return make_uint4((uint32_t)a, (uint32_t)(a >> 32), (uint32_t)b, (uint32_t)(b >> 32));
}

#define TSTAMP(i)
#define PSTAMP(i)
#define WSTAMP(i, dep)

template <int S>
__global__ void __launch_bounds__(NTHREADS, 1)
decode_kernel(const __grid_constant__ CUtensorMap tmKA, const __grid_constant__ CUtensorMap tmVA,
              const __grid_constant__ CUtensorMap tmKB, const __grid_constant__ CUtensorMap tmVB,
              const __grid_constant__ CUtensorMap tmWqA, const __grid_constant__ CUtensorMap tmWqB,
              const __grid_constant__ CUtensorMap tmWoA, const __grid_constant__ CUtensorMap tmWoB,
              const Params prm)
{
    using L = Smem<S>;
    constexpr int W0 = DK_WIN0 < S ? DK_WIN0 : S, WN = DK_WIN < S ? DK_WIN : S;
    extern __shared__ char smem_raw[];
    const uint32_t base = (smem_u32(smem_raw) + 1023u) & ~1023u;
    char* sm = smem_raw + (base - smem_u32(smem_raw));
    const uint32_t fullb = base + L::bars, emptyb = fullb + 8 * S;
    volatile uint32_t* const flags = reinterpret_cast<volatile uint32_t*>(sm + L::ml + 64);

    const int tid = threadIdx.x, warp = tid >> 5, lane = tid & 31;
    const int j = blockIdx.x;
    const int grp = j >> 3, r = j & 7;
    const int pj = j >> 6, sj = j & 63;

    TSTAMP(0);
    if (DK_PREFETCH & 1) {
        const char* w = reinterpret_cast<const char*>(pj ? prm.wqB : prm.wqA) + sj * 128;
        #pragma unroll
        for (int k = 0; k < 3; k++) {
            const int row = tid + k * 192;
            if (tid < 192 && row < ((DK_PREFETCH & 8) ? 224 : 448)) asm volatile("prefetch.global.L2 [%0];" ::"l"(w + (size_t)row * 8192) : "memory");
        }
    }
    if ((DK_PREFETCH & 2) && tid == 0) {
        const size_t off = (size_t)(grp * 8192 + 6144 + (DK_RR ? r * 64 : r * NT_B * 64)) * 512;
        asm volatile("cp.async.bulk.prefetch.L2.global [%0], %1;" ::"l"(reinterpret_cast<const char*>(prm.kB) + off), "r"(SLOT) : "memory");
        if (DK_PREFETCH & 4)
            asm volatile("cp.async.bulk.prefetch.L2.global [%0], %1;" ::"l"(reinterpret_cast<const char*>(prm.vB) + off), "r"(SLOT) : "memory");
    }
    uint32_t tag;
    asm volatile("ld.relaxed.gpu.global.u32 %0, [%1];" : "=r"(tag) : "l"(prm.epoch) : "memory");
    const uint4* msrc = prm.part + ((((pj * 16 + (sj >> 2)) * 4 + (sj & 3)) * 2 + (warp & 1)) * 8) * 32 + lane;
    pin(msrc);
    if (warp == 4) {
        const CUtensorMap* tmWq = pj ? &tmWqB : &tmWqA;
        const CUtensorMap* tmWo = pj ? &tmWoB : &tmWoA;
        uint64_t pol = 0;
        auto issue = [&](int i, int slot) {
            const uint32_t bar = fullb + 8 * slot, dst = base + L::ring + slot * SLOT;
            if (i < 2) {
                mbar_expect_tx(bar, WQ_BYTES + (i == 0 ? X_BYTES : 0));
                tma2d(dst, tmWq, sj * 64, i * 224, bar, pol);
                if (i == 0) bulk1d(base + L::xs, pj ? prm.xB : prm.xA, X_BYTES, bar);
            } else if (i < NITEMS - 2) {
                const int k = i - 2, t = k >> 1, isV = k & 1;
                int row; const CUtensorMap* tm;
                if (t < NT_B) {
                    row = grp * 8192 + 6144 + (DK_RR ? (t * 8 + r) * 64 : (r * NT_B + t) * 64);
                    tm = isV ? &tmVB : &tmKB;
                } else {
                    const int ta = t - NT_B;
                    row = grp * 8192 + (DK_RR ? (ta * 8 + r) * 64 : (r * NT_A + ta) * 64);
                    tm = isV ? &tmVA : &tmKA;
                }
                mbar_expect_tx(bar, SLOT);
                tma3d(dst, tm, 0, row, 0, bar, pol);
            } else {
                mbar_expect_tx(bar, SLOT);
                tma3d(dst, tmWo, 0, sj * 64, (i - (NITEMS - 2)) * 4, bar, pol);
            }
        };
        auto l2ahead = [&](int i) {
            const int k = i - 2, t = k >> 1, isV = k & 1;
            const __nv_bfloat16* src;
            if (t < NT_B) src = (isV ? prm.vB : prm.kB) + (size_t)(grp * 8192 + 6144 + (r * NT_B + t) * 64) * 256;
            else          src = (isV ? prm.vA : prm.kA) + (size_t)(grp * 8192 + (r * NT_A + t - NT_B) * 64) * 256;
            asm volatile("cp.async.bulk.prefetch.L2.global.L2::cache_hint [%0], %1, %2;" ::"l"(src), "r"(SLOT), "l"(pol) : "memory");
        };
        if (lane == 0) {
            PSTAMP(0);
            for (int s = 0; s < S; s++) { mbar_init(fullb + 8 * s, 1); mbar_init(emptyb + 8 * s, 4); }
            if (DK_CX) { flags[0] = 0; flags[1] = 0; }
            asm volatile("fence.mbarrier_init.release.cluster;" ::: "memory");
            asm volatile("createpolicy.fractional.L2::evict_first.b64 %0, 1.0;" : "=l"(pol));
            PSTAMP(1);
            #pragma unroll 1
            for (int i = 0; i < W0; i++) {
                issue(i, i);
                if (i == 0) PSTAMP(2);
                if (i == 1) { prefetch_map(&tmKB); prefetch_map(&tmVB); }
            }
            PSTAMP(3);
            prefetch_map(&tmKA); prefetch_map(&tmVA); prefetch_map(tmWo);
        }
        __syncthreads();
        if (lane == 0) {
            int slot = W0 == S ? 0 : W0; uint32_t ph = W0 == S ? 0 : 1;
            #pragma unroll 1
            for (int i = W0; i < NITEMS; i++) {
                const int w = i < DK_N0 ? W0 : (i >= NITEMS - 2 ? DK_WWO : (i >= NITEMS - 2 - DK_NE ? DK_WE : WN));
                if (w < S) { const int k = i - w; mbar_wait(fullb + 8 * (k % S), (k / S) & 1); }
                if (DK_RA1 > DK_RA0 && i + DK_RAD >= DK_RA0 && i + DK_RAD < DK_RA1) l2ahead(i + DK_RAD);
                mbar_wait(emptyb + 8 * slot, ph);
                if (DK_CX && i == NITEMS - 2) {
                    const long long t0 = clock64();
                    while (flags[1] == 0) if (clock64() - t0 > SPIN_LIMIT) __trap();
                }
                issue(i, slot);
                if (DK_CX && i == DK_CX) {
                    asm volatile("red.relaxed.gpu.global.add.u32 [%0], 1;" ::"l"(prm.epoch + 32) : "memory");
                    flags[0] = 1;
                }
                if (++slot == S) { slot = 0; ph ^= 1; }
            }
            mbar_wait(fullb + 8 * ((NITEMS - 3) % S), ((NITEMS - 3) / S) & 1);
        }
        __syncwarp();
    } else if (warp == 5) {
        __syncthreads();
        if (DK_CX && lane == 0) {
            const long long t0 = clock64();
            while (flags[0] == 0) { __nanosleep(200); if (clock64() - t0 > SPIN_LIMIT) __trap(); }
            while (true) {
                uint32_t v;
                asm volatile("ld.relaxed.gpu.global.u32 %0, [%1];" : "=r"(v) : "l"(prm.epoch + 32) : "memory");
                if ((int)(v - (tag * NCTA + DK_CT)) >= 0) break;
                if (clock64() - t0 > SPIN_LIMIT) __trap();
                __nanosleep(DK_CSLEEP);
            }
            flags[1] = 1;
        }
        __syncwarp();
    }
    if (warp == 4 || warp == 5) {
        asm volatile("bar.sync 3, 64;" ::: "memory");
        tag += 1;
        uint4 v[8];
        #pragma unroll
        for (int i = 0; i < 8; i++) v[i] = ld_ll16(msrc + i * 32);
        for (uint32_t it = 0;; it++) {
            const uint32_t bad = (((v[0].w ^ tag) | (v[1].w ^ tag)) | ((v[2].w ^ tag) | (v[3].w ^ tag))) |
                                 (((v[4].w ^ tag) | (v[5].w ^ tag)) | ((v[6].w ^ tag) | (v[7].w ^ tag)));
            if (__all_sync(0xffffffffu, bad == 0)) break;
            #pragma unroll
            for (int i = 0; i < 8; i++)
                if (!DK_PRED || v[i].w != tag) v[i] = ld_ll16(msrc + i * 32);
            if (it > POLL_LIMIT) __trap();
        }
        WSTAMP(1, v[0].x);
        float l[8], w[8];
        #pragma unroll
        for (int i = 0; i < 8; i++) l[i] = __uint_as_float(v[i].z);
        const float M = fmaxf(fmaxf(fmaxf(l[0], l[1]), fmaxf(l[2], l[3])), fmaxf(fmaxf(l[4], l[5]), fmaxf(l[6], l[7])));
        #pragma unroll
        for (int i = 0; i < 8; i++) w[i] = ex2(l[i] - M);
        float oa[2], ob[2];
        #pragma unroll
        for (int h = 0; h < 2; h++) {
            oa[h] = w[4 * h] * __uint_as_float(v[4 * h].x);
            ob[h] = w[4 * h] * __uint_as_float(v[4 * h].y);
            #pragma unroll
            for (int i = 4 * h + 1; i < 4 * h + 4; i++) {
                oa[h] = fmaf(w[i], __uint_as_float(v[i].x), oa[h]);
                ob[h] = fmaf(w[i], __uint_as_float(v[i].y), ob[h]);
            }
        }
        const float inv = rcp(((w[0] + w[1]) + (w[2] + w[3])) + ((w[4] + w[5]) + (w[6] + w[7])));
        const uint32_t res = pack_bf16((oa[0] + oa[1]) * inv, (ob[0] + ob[1]) * inv);
        reinterpret_cast<uint32_t*>(sm + L::os)[(warp - 4) * 32 + lane] = res;
        asm volatile("bar.arrive 2, 192;" ::: "memory");
        return;
    }
    const int g = lane >> 2, t4 = lane & 3;
    const int bq = grp >> 3, hkv = grp & 7;
    uint2* pubq = prm.q + (pj * 2 + (t4 & 1)) * 2048 + sj * 32 + warp * 8 + (t4 >> 1) * 4 + (g >> 1);
    uint4* pubp = prm.part + ((((hkv * 2) * 4 + warp) * 2 + bq) * 8 + r) * 32 + lane;
    uint4* pubo = prm.outp + ((pj * 56 + t4 * 8 + warp * 2) * 64 + sj) * 8 + g;
    constexpr int PP = 16 * 4 * 2 * 8 * 32, PH = 4 * 2 * 8 * 32, OB = 64 * 8;
    const uint4* fsrc = prm.outp + j * OB + warp * 128 + lane;
    __nv_bfloat16* fout = prm.out + (tid >> 3) * 896 + (j >= 56 ? 448 + (j - 56) * 8 : j * 8) + (tid & 7);
    unsigned* epoch = prm.epoch;
    pin(pubp); pin(pubo); pin(fsrc); pin(fout); pin(epoch);
    if (!(g & 1)) st_ll8(pubq, 0, 0);
    st_ll16(pubp, 0, 0, 0, 0); st_ll16(pubp + PH, 0, 0, 0, 0);
    st_ll16(pubp + PP, 0, 0, 0, 0); st_ll16(pubp + PP + PH, 0, 0, 0, 0);
    st_ll16(pubo, 0, 0, 0, 0); st_ll16(pubo + OB, 0, 0, 0, 0);
    if (t4 < 3) { st_ll16(pubo + 32 * OB, 0, 0, 0, 0); st_ll16(pubo + 33 * OB, 0, 0, 0, 0); }
    __syncthreads();
    tag += 1;

    int slot = 0; uint32_t ph = 0;
    auto advance = [&]() { if (++slot == S) { slot = 0; ph ^= 1; } };
    auto release = [&]() { __syncwarp(); if (lane == 0) mbar_arrive(emptyb + 8 * slot); };

    const uint32_t l7 = lane & 7;
    const uint32_t offT = (l7 + (lane >> 4) * 8) * 128 + ((((lane >> 3) & 1) ^ l7) << 4);
    const uint32_t offP = (l7 + ((lane >> 3) & 1) * 8) * 128 + (((lane >> 4) ^ l7) << 4);

    {
        float c0[4] = {0.f, 0.f, 0.f, 0.f}, c1[4] = {0.f, 0.f, 0.f, 0.f};
        const uint32_t xa = base + L::xs + (g & 1) * 896 + t4 * 4;
        #pragma unroll
        for (int h = 0; h < 2; h++) {
            mbar_wait(fullb + 8 * slot, ph);
            const uint32_t tb = base + L::ring + slot * SLOT + (offT ^ (warp << 5));
            #pragma unroll
            for (int ks = 0; ks < 14; ks++) {
                uint32_t a[4];
                ldsm4t(a, tb + ks * 2048);
                const uint32_t b0 = lds32(xa + (h * 14 + ks) * 32), b1 = lds32(xa + (h * 14 + ks) * 32 + 16);
                if (ks & 1) mma16816(c1, a, b0, b1); else mma16816(c0, a, b0, b1);
            }
            release();
            advance();
        }
        TSTAMP(1);
        const float lo = (t4 & 1) ? c0[1] + c1[1] : c0[0] + c1[0], hi = (t4 & 1) ? c0[3] + c1[3] : c0[2] + c1[2];
        const float v = (t4 & 2) ? hi : lo;
        const float vn = __shfl_xor_sync(0xffffffffu, v, 4);
        if (!(g & 1)) st_ll8(pubq, pack_bf16(v, vn), tag);
    }
    {
        const uint2* s0 = prm.q + bq * 2048 + hkv * 256 + tid * 2;
        const uint2* s1 = s0 + 2 * 2048;
        uint4 v0, v1;
        v0 = ld_ll8x2(s0);
        v1 = ld_ll8x2(s1);
        for (uint32_t it = 0; !__all_sync(0xffffffffu, v0.y == tag && v0.w == tag && v1.y == tag && v1.w == tag); it++) {
            if (!DK_PRED || v0.y != tag || v0.w != tag) v0 = ld_ll8x2(s0);
            if (!DK_PRED || v1.y != tag || v1.w != tag) v1 = ld_ll8x2(s1);
            if (it > POLL_LIMIT) __trap();
        }
        uint2* qs = reinterpret_cast<uint2*>(sm + L::qs);
        qs[tid] = make_uint2(v0.x, v0.z);
        qs[128 + tid] = make_uint2(v1.x, v1.z);
        cons_sync();
    }
    TSTAMP(2);

    constexpr float CS = 1.4426950408889634f / 16.0f;
    #pragma unroll 1
    for (int pi = 0; pi < 2; pi++) {
        const int p = 1 - pi;
        const int ntiles = p ? NT_B : NT_A;
        uint32_t qf[16][2];
        {
            const uint32_t qa = base + L::qs + p * 1024 + (g & 1) * 512 + t4 * 4;
            #pragma unroll
            for (int ks = 0; ks < 16; ks++) {
                qf[ks][0] = lds32(qa + ks * 32);
                qf[ks][1] = lds32(qa + ks * 32 + 16);
            }
        }
        float o[4][4], ls[4] = {0.f, 0.f, 0.f, 0.f};
        #pragma unroll
        for (int i = 0; i < 4; i++) { o[i][0] = 0.f; o[i][1] = 0.f; o[i][2] = 0.f; o[i][3] = 0.f; }
        float m0 = -INFINITY, m1 = -INFINITY;

        #pragma unroll 1
        for (int t = 0; t < ntiles; t++) {
            mbar_wait(fullb + 8 * slot, ph);
            float sa[4] = {0.f, 0.f, 0.f, 0.f}, sb[4] = {0.f, 0.f, 0.f, 0.f};
            {
                const uint32_t kb = base + L::ring + slot * SLOT + warp * 2048;
                #pragma unroll
                for (int ks = 0; ks < 16; ks++) {
                    uint32_t a[4];
                    ldsm4(a, kb + (ks >> 2) * 8192 + (offP ^ ((ks & 3) << 5)));
                    if (ks & 1) mma16816(sb, a, qf[ks][0], qf[ks][1]); else mma16816(sa, a, qf[ks][0], qf[ks][1]);
                }
            }
            release();
            advance();
            const float s0 = sa[0] + sb[0], s1 = sa[1] + sb[1], s2 = sa[2] + sb[2], s3 = sa[3] + sb[3];
            float x0 = fmaxf(s0, s2), x1 = fmaxf(s1, s3);
            #pragma unroll
            for (int d = 4; d < 32; d <<= 1) {
                x0 = fmaxf(x0, __shfl_xor_sync(0xffffffffu, x0, d));
                x1 = fmaxf(x1, __shfl_xor_sync(0xffffffffu, x1, d));
            }
            if (__any_sync(0xffffffffu, x0 > m0 || x1 > m1)) {
                const float n0 = fmaxf(m0, x0), n1 = fmaxf(m1, x1);
                const float f0 = ex2((m0 - n0) * CS), f1 = ex2((m1 - n1) * CS);
                m0 = n0; m1 = n1;
                ls[0] *= f0; ls[1] *= f1;
                #pragma unroll
                for (int i = 0; i < 4; i++) { o[i][0] *= f0; o[i][1] *= f1; o[i][2] *= f0; o[i][3] *= f1; }
            }
            const float mc0 = m0 * CS, mc1 = m1 * CS;
            const float p0 = ex2(fmaf(s0, CS, -mc0)), p1 = ex2(fmaf(s1, CS, -mc1));
            const float p2 = ex2(fmaf(s2, CS, -mc0)), p3 = ex2(fmaf(s3, CS, -mc1));
            const uint32_t pb0 = movmat(pack_bf16(p0, p1)), pb1 = movmat(pack_bf16(p2, p3));
            {
                const uint32_t ones[4] = {0x3F803F80u, 0x3F803F80u, 0x3F803F80u, 0x3F803F80u};
                mma16816(ls, ones, pb0, pb1);
            }
            mbar_wait(fullb + 8 * slot, ph);
            {
                const uint32_t vb = base + L::ring + slot * SLOT + warp * 2048;
                #pragma unroll
                for (int u = 0; u < 4; u++) {
                    const uint32_t q0 = (g >> 1) == u ? pb0 : 0u, q1 = (g >> 1) == u ? pb1 : 0u;
                    #pragma unroll
                    for (int a4 = 0; a4 < 4; a4++) {
                        uint32_t a[4];
                        ldsm4t(a, vb + a4 * 8192 + (offT ^ (u << 5)));
                        mma16816(o[a4], a, q0, q1);
                    }
                }
            }
            release();
            advance();
            if (pi == 0 && t == 0) TSTAMP(3);
        }
        TSTAMP(pi == 0 ? 4 : 6);

        {
            float2* rw = reinterpret_cast<float2*>(sm + L::red) + warp * 320 + t4 * 20 + g;
            #pragma unroll
            for (int a4 = 0; a4 < 4; a4++) {
                rw[a4 * 80]     = make_float2(o[a4][0], o[a4][1]);
                rw[a4 * 80 + 8] = make_float2(o[a4][2], o[a4][3]);
            }
            if (lane == 0) reinterpret_cast<float4*>(sm + L::ml)[warp] = make_float4(m0 * CS, m1 * CS, ls[0], ls[1]);
        }
        cons_sync();
        {
            const float4* ml = reinterpret_cast<const float4*>(sm + L::ml);
            const float4 w0 = ml[0], w1 = ml[1], w2 = ml[2], w3 = ml[3];
            const float4* r4 = reinterpret_cast<const float4*>(sm + L::red) + (tid >> 3) * 10 + (tid & 7);
            const float4 a0 = r4[0], a1 = r4[160], a2 = r4[320], a3 = r4[480];
            const float M0 = fmaxf(fmaxf(w0.x, w1.x), fmaxf(w2.x, w3.x));
            const float M1 = fmaxf(fmaxf(w0.y, w1.y), fmaxf(w2.y, w3.y));
            const float e00 = ex2(w0.x - M0), e01 = ex2(w1.x - M0), e02 = ex2(w2.x - M0), e03 = ex2(w3.x - M0);
            const float e10 = ex2(w0.y - M1), e11 = ex2(w1.y - M1), e12 = ex2(w2.y - M1), e13 = ex2(w3.y - M1);
            const float L0 = (e00 * w0.z + e01 * w1.z) + (e02 * w2.z + e03 * w3.z);
            const float L1 = (e10 * w0.w + e11 * w1.w) + (e12 * w2.w + e13 * w3.w);
            const float i0 = rcp(L0), i1 = rcp(L1);
            const float lse0 = M0 + lg2(L0), lse1 = M1 + lg2(L1);
            const float h0a = ((e00 * a0.x + e01 * a1.x) + (e02 * a2.x + e03 * a3.x)) * i0;
            const float h0b = ((e00 * a0.z + e01 * a1.z) + (e02 * a2.z + e03 * a3.z)) * i0;
            const float h1a = ((e10 * a0.y + e11 * a1.y) + (e12 * a2.y + e13 * a3.y)) * i1;
            const float h1b = ((e10 * a0.w + e11 * a1.w) + (e12 * a2.w + e13 * a3.w)) * i1;
            uint4* dst = pubp + p * PP;
            WSTAMP(0, __float_as_uint(h1b));
            st_ll16(dst, __float_as_uint(h0a), __float_as_uint(h0b), __float_as_uint(lse0), tag);
            st_ll16(dst + PH, __float_as_uint(h1a), __float_as_uint(h1b), __float_as_uint(lse1), tag);
        }
        TSTAMP(pi == 0 ? 5 : 7);
    }

    {
        uint32_t wf[7][4][4];
        #pragma unroll
        for (int h = 0; h < 2; h++) {
            constexpr int I0 = NITEMS - 2;
            mbar_wait(fullb + 8 * ((I0 + h) % S), ((I0 + h) / S) & 1);
            const uint32_t wb = base + L::ring + ((I0 + h) % S) * SLOT + (offT ^ (warp << 5));
            #pragma unroll
            for (int c = 0; c < 4 - h; c++)
                #pragma unroll
                for (int ks = 0; ks < 4; ks++) ldsm4t(wf[h * 4 + c][ks], wb + c * 8192 + ks * 2048);
        }
        TSTAMP(9);
        asm volatile("bar.sync 2, 192;" ::: "memory");
        uint32_t of[4][2];
        const uint32_t oa = base + L::os + (g & 1) * 128 + t4 * 4;
        #pragma unroll
        for (int ks = 0; ks < 4; ks++) {
            of[ks][0] = lds32(oa + ks * 32);
            of[ks][1] = lds32(oa + ks * 32 + 16);
        }
        WSTAMP(2, of[3][1]);
        float acc[7][4];
        #pragma unroll
        for (int c = 0; c < 7; c++) { acc[c][0] = 0.f; acc[c][1] = 0.f; acc[c][2] = 0.f; acc[c][3] = 0.f; }
        #pragma unroll
        for (int ks = 0; ks < 4; ks++)
            #pragma unroll
            for (int c = 0; c < 7; c++) mma16816(acc[c], wf[c][ks], of[ks][0], of[ks][1]);
        float e[4], f[4];
        #pragma unroll
        for (int i = 0; i < 4; i++) {
            const float x = (t4 & 1) ? acc[1][i] : acc[0][i], y = (t4 & 1) ? acc[3][i] : acc[2][i];
            e[i] = (t4 & 2) ? y : x;
            const float z = (t4 & 1) ? acc[5][i] : acc[4][i];
            f[i] = (t4 & 2) ? acc[6][i] : z;
        }
        WSTAMP(3, __float_as_uint(e[3]));
        st_ll16(pubo, __float_as_uint(e[0]), __float_as_uint(e[1]), tag, 0u);
        st_ll16(pubo + OB, __float_as_uint(e[2]), __float_as_uint(e[3]), tag, 0u);
        if (t4 < 3) {
            st_ll16(pubo + 32 * OB, __float_as_uint(f[0]), __float_as_uint(f[1]), tag, 0u);
            st_ll16(pubo + 33 * OB, __float_as_uint(f[2]), __float_as_uint(f[3]), tag, 0u);
        }
        WSTAMP(4, tag);
    }
    TSTAMP(10);

    if (j < 112) {
        uint4 va[4];
        #pragma unroll
        for (int i = 0; i < 4; i++) va[i] = ld_ll16(fsrc + i * 32);
        WSTAMP(5, va[3].z + 12345);
        for (uint32_t it = 0;; it++) {
            const uint32_t bad = ((va[0].z ^ tag) | (va[1].z ^ tag)) | ((va[2].z ^ tag) | (va[3].z ^ tag));
            if (__all_sync(0xffffffffu, bad == 0)) break;
            #pragma unroll
            for (int i = 0; i < 4; i++)
                if (!DK_PRED || va[i].z != tag) va[i] = ld_ll16(fsrc + i * 32);
            if (it > POLL_LIMIT) __trap();
        }
        WSTAMP(6, va[0].x);
        float a = (__uint_as_float(va[0].x) + __uint_as_float(va[1].x)) + (__uint_as_float(va[2].x) + __uint_as_float(va[3].x));
        float b = (__uint_as_float(va[0].y) + __uint_as_float(va[1].y)) + (__uint_as_float(va[2].y) + __uint_as_float(va[3].y));
        #pragma unroll
        for (int d = 8; d < 32; d <<= 1) {
            a += __shfl_xor_sync(0xffffffffu, a, d);
            b += __shfl_xor_sync(0xffffffffu, b, d);
        }
        float* fr = reinterpret_cast<float*>(sm + L::red);
        if (lane < 16) fr[warp * 16 + lane] = lane < 8 ? a : b;
        cons_sync();
        if (tid < 16) {
            const float v = (fr[tid] + fr[16 + tid]) + (fr[32 + tid] + fr[48 + tid]);
            WSTAMP(7, __float_as_uint(v));
            *fout = __float2bfloat16_rn(v);
            if (j == 0 && tid == 0)
                asm volatile("st.relaxed.gpu.global.u32 [%0], %1;" ::"l"(epoch), "r"(tag) : "memory");
        }
    }
    TSTAMP(11);
}

typedef CUresult (*EncodeFn)(CUtensorMap*, CUtensorMapDataType, cuuint32_t, void*, const cuuint64_t*, const cuuint64_t*,
                             const cuuint32_t*, const cuuint32_t*, CUtensorMapInterleave, CUtensorMapSwizzle,
                             CUtensorMapL2promotion, CUtensorMapFloatOOBfill);

inline CUtensorMap make_map(EncodeFn enc, const void* ptr, int rank, const cuuint64_t* dims, const cuuint64_t* strides, const cuuint32_t* box) {
    CUtensorMap m;
    const cuuint32_t es[3] = {1, 1, 1};
    enc(&m, CU_TENSOR_MAP_DATA_TYPE_BFLOAT16, rank, const_cast<void*>(ptr), dims, strides, box, es,
        CU_TENSOR_MAP_INTERLEAVE_NONE, CU_TENSOR_MAP_SWIZZLE_128B, CU_TENSOR_MAP_L2_PROMOTION_NONE,
        CU_TENSOR_MAP_FLOAT_OOB_FILL_NONE);
    return m;
}

}

extern "C" void kernel_launch(void* const* d_in, const int* in_sizes, int n_in, void* d_out, int out_size) {
    using namespace dk;
    (void)in_sizes; (void)n_in; (void)out_size;
    void* fn = nullptr;
    cudaDriverEntryPointQueryResult qr;
    cudaGetDriverEntryPoint("cuTensorMapEncodeTiled", &fn, cudaEnableDefault, &qr);
    EncodeFn enc = (EncodeFn)fn;

    const cuuint64_t kvd[3] = {64, 131072, 4}, kvs[2] = {512, 128};
    const cuuint32_t kvb[3] = {64, 64, 4};
    const cuuint64_t wqd[2] = {4096, 448}, wqs[1] = {8192};
    const cuuint32_t wqb[2] = {64, 224};
    const cuuint64_t wod[3] = {64, 4096, 7}, wos[2] = {896, 128};
    const cuuint32_t wob[3] = {64, 64, 4};
    const CUtensorMap kA = make_map(enc, d_in[1], 3, kvd, kvs, kvb), vA = make_map(enc, d_in[2], 3, kvd, kvs, kvb);
    const CUtensorMap kB = make_map(enc, d_in[6], 3, kvd, kvs, kvb), vB = make_map(enc, d_in[7], 3, kvd, kvs, kvb);
    const CUtensorMap wqA = make_map(enc, d_in[3], 2, wqd, wqs, wqb), wqB = make_map(enc, d_in[8], 2, wqd, wqs, wqb);
    const CUtensorMap woA = make_map(enc, d_in[4], 3, wod, wos, wob), woB = make_map(enc, d_in[9], 3, wod, wos, wob);
    Params prm;
    prm.xA = (const __nv_bfloat16*)d_in[0];
    prm.xB = (const __nv_bfloat16*)d_in[5];
    prm.wqA = (const __nv_bfloat16*)d_in[3];
    prm.wqB = (const __nv_bfloat16*)d_in[8];
    prm.kB = (const __nv_bfloat16*)d_in[6];
    prm.vB = (const __nv_bfloat16*)d_in[7];
    prm.kA = (const __nv_bfloat16*)d_in[1];
    prm.vA = (const __nv_bfloat16*)d_in[2];
    prm.out = (__nv_bfloat16*)d_out;
    void* a = nullptr;
    cudaGetSymbolAddress(&a, g_epoch); prm.epoch = (unsigned*)a;
    cudaGetSymbolAddress(&a, g_q);     prm.q = (uint2*)a;
    cudaGetSymbolAddress(&a, g_part);  prm.part = (uint4*)a;
    cudaGetSymbolAddress(&a, g_out);   prm.outp = (uint4*)a;

    constexpr int S = DK_STAGES;
    cudaFuncSetAttribute(decode_kernel<S>, cudaFuncAttributeMaxDynamicSharedMemorySize, Smem<S>::total);
    decode_kernel<S><<<NCTA, NTHREADS, Smem<S>::total>>>(kA, vA, kB, vB, wqA, wqB, woA, woB, prm);
}
```

```cpp
#include <cuda_runtime.h>
#include <cuda.h>
#include <cuda_bf16.h>
#include <stdint.h>

namespace dk8 {

constexpr int NMAIN    = 64;
constexpr int NHELP    = 56;
constexpr int NCTA     = NMAIN + NHELP;
constexpr int NTHREADS = 224;
constexpr int S        = 6;
constexpr int SLOT     = 32768;
constexpr int NT_B     = 8;
constexpr int NT_A     = 32;
constexpr int NWQ      = 4;
constexpr int NKV      = NWQ + 2 * (NT_A + NT_B);
constexpr int NI       = NKV + 2;
constexpr int WQ_BYTES = 224 * 128;
constexpr int X_BYTES  = 2 * 448 * 2;
constexpr int WO_BYTES = 32 * 896;
constexpr int WIN      = 5;
constexpr int WIN_WO   = 4;
constexpr int IW0 = 84, IW1 = 85;
constexpr int PACE     = 48;
constexpr int IEV      = 82;
constexpr int REL0 = 16, REL1 = 48;
constexpr uint32_t TM = 7;
constexpr int NWB = 8;
constexpr int OBS = 1024 + 32;
constexpr int SCS = 80;
constexpr int PBS = 1024 + 64;
constexpr int PSZ = 2 * PBS + 64;
constexpr long long SPIN_LIMIT = 4000000000LL;

struct Smem {
    static constexpr int ring = 0;
    static constexpr int obs  = 3 * SLOT;
    static constexpr int fb   = 2 * SLOT;
    static constexpr int red  = S * SLOT;
    static constexpr int sc   = red + 1024;
    static constexpr int flg  = sc + 4 * SCS * 4;
    static constexpr int xs   = flg + 128;
    static constexpr int qs   = xs + 2 * X_BYTES;
    static constexpr int part = qs + 2048;
    static constexpr int bars = part + 2 * PSZ;
    static constexpr int total = bars + 16 * S + 128 + 1024;
};

struct Params {
    const __nv_bfloat16* wqB;
    const __nv_bfloat16* wqA;
    unsigned* epoch;
    const __nv_bfloat16* xA;
    const __nv_bfloat16* xB;
    uint4* outp;
    uint2* ob;
    __nv_bfloat16* out;
    uint2* hello;
};

__device__ __align__(128) unsigned g_epoch[96];
__device__ __align__(128) uint4 g_out[56][64][4];
__device__ __align__(128) uint2 g_ob[2][2048];
__device__ __align__(128) uint2 g_hello[64];

__device__ __forceinline__ uint32_t smem_u32(const void* p) { return (uint32_t)__cvta_generic_to_shared(p); }
__device__ __forceinline__ void mbar_init(uint32_t bar, uint32_t cnt) {
    asm volatile("mbarrier.init.shared::cta.b64 [%0], %1;" ::"r"(bar), "r"(cnt) : "memory");
}
__device__ __forceinline__ void mbar_expect_tx(uint32_t bar, uint32_t bytes) {
    asm volatile("mbarrier.arrive.expect_tx.shared::cta.b64 _, [%0], %1;" ::"r"(bar), "r"(bytes) : "memory");
}
__device__ __forceinline__ void mbar_arrive(uint32_t bar) {
    asm volatile("mbarrier.arrive.shared::cta.b64 _, [%0];" ::"r"(bar) : "memory");
}
__device__ __forceinline__ bool mbar_try(uint32_t bar, uint32_t parity) {
    uint32_t ok;
    asm volatile("{\n.reg .pred p;\nmbarrier.try_wait.parity.shared::cta.b64 p, [%1], %2;\nselp.u32 %0, 1, 0, p;\n}"
                 : "=r"(ok) : "r"(bar), "r"(parity) : "memory");
    return ok != 0;
}
__device__ __forceinline__ bool mbar_test(uint32_t bar, uint32_t parity) {
    uint32_t ok;
    asm volatile("{\n.reg .pred p;\nmbarrier.test_wait.parity.shared::cta.b64 p, [%1], %2;\nselp.u32 %0, 1, 0, p;\n}"
                 : "=r"(ok) : "r"(bar), "r"(parity) : "memory");
    return __all_sync(0xffffffffu, ok != 0);
}
__device__ __forceinline__ bool mbar_test_cluster(uint32_t bar, uint32_t parity) {
    uint32_t ok;
    asm volatile("{\n.reg .pred p;\nmbarrier.test_wait.parity.acquire.cluster.shared::cta.b64 p, [%1], %2;\nselp.u32 %0, 1, 0, p;\n}"
                 : "=r"(ok) : "r"(bar), "r"(parity) : "memory");
    return __all_sync(0xffffffffu, ok != 0);
}
__device__ __forceinline__ void mbar_wait(uint32_t bar, uint32_t parity) {
    if (mbar_try(bar, parity)) return;
    const long long t0 = clock64();
    while (!mbar_try(bar, parity))
        if (clock64() - t0 > SPIN_LIMIT) __trap();
}
template <typename T> __device__ __forceinline__ void pin(T*& p) { asm volatile("" : "+l"(p)); }
constexpr uint32_t POLL_LIMIT = 1u << 24;
__device__ __forceinline__ void cons_sync() { asm volatile("bar.sync 1, 128;" ::: "memory"); }
__device__ __forceinline__ void start_sync() {
    __syncthreads();
    asm volatile("barrier.cluster.arrive.relaxed.aligned;" ::: "memory");
}
__device__ __forceinline__ uint32_t mapa(uint32_t addr, uint32_t rank) {
    uint32_t r;
    asm("mapa.shared::cluster.u32 %0, %1, %2;" : "=r"(r) : "r"(addr), "r"(rank));
    return r;
}
__device__ __forceinline__ void st_async16(uint32_t addr, uint32_t a, uint32_t b, uint32_t c, uint32_t d, uint32_t bar) {
    asm volatile("st.async.weak.shared::cluster.mbarrier::complete_tx::bytes.v4.b32 [%0], {%1, %2, %3, %4}, [%5];"
                 ::"r"(addr), "r"(a), "r"(b), "r"(c), "r"(d), "r"(bar) : "memory");
}
__device__ __forceinline__ void st_async8(uint32_t addr, uint32_t a, uint32_t b, uint32_t bar) {
    asm volatile("st.async.weak.shared::cluster.mbarrier::complete_tx::bytes.v2.b32 [%0], {%1, %2}, [%3];"
                 ::"r"(addr), "r"(a), "r"(b), "r"(bar) : "memory");
}
__device__ __forceinline__ void mbar_wait_cluster(uint32_t bar, uint32_t parity) {
    const long long t0 = clock64();
    for (;;) {
        uint32_t ok;
        asm volatile("{\n.reg .pred p;\nmbarrier.try_wait.parity.acquire.cluster.shared::cta.b64 p, [%1], %2;\nselp.u32 %0, 1, 0, p;\n}"
                     : "=r"(ok) : "r"(bar), "r"(parity) : "memory");
        if (ok) return;
        if (clock64() - t0 > SPIN_LIMIT) __trap();
    }
}

__device__ __forceinline__ void tma2d(uint32_t dst, const CUtensorMap* tm, int c0, int c1, uint32_t bar, uint64_t pol) {
    asm volatile("cp.async.bulk.tensor.2d.shared::cluster.global.mbarrier::complete_tx::bytes.L2::cache_hint [%0], [%1, {%3, %4}], [%2], %5;"
                 ::"r"(dst), "l"(tm), "r"(bar), "r"(c0), "r"(c1), "l"(pol) : "memory");
}
__device__ __forceinline__ void tma3d(uint32_t dst, const CUtensorMap* tm, int c0, int c1, int c2, uint32_t bar, uint64_t pol) {
    asm volatile("cp.async.bulk.tensor.3d.shared::cluster.global.mbarrier::complete_tx::bytes.L2::cache_hint [%0], [%1, {%3, %4, %5}], [%2], %6;"
                 ::"r"(dst), "l"(tm), "r"(bar), "r"(c0), "r"(c1), "r"(c2), "l"(pol) : "memory");
}
__device__ __forceinline__ void bulk1d(uint32_t dst, const void* src, uint32_t bytes, uint32_t bar) {
    asm volatile("cp.async.bulk.shared::cluster.global.mbarrier::complete_tx::bytes [%0], [%1], %2, [%3];"
                 ::"r"(dst), "l"(src), "r"(bytes), "r"(bar) : "memory");
}
__device__ __forceinline__ void prefetch_map(const CUtensorMap* tm) {
    asm volatile("prefetch.tensormap [%0];" ::"l"(tm) : "memory");
}

__device__ __forceinline__ void ldsm4(uint32_t (&r)[4], uint32_t addr) {
    asm volatile("ldmatrix.sync.aligned.m8n8.x4.shared.b16 {%0,%1,%2,%3}, [%4];"
                 : "=r"(r[0]), "=r"(r[1]), "=r"(r[2]), "=r"(r[3]) : "r"(addr) : "memory");
}
__device__ __forceinline__ void ldsm4t(uint32_t (&r)[4], uint32_t addr) {
    asm volatile("ldmatrix.sync.aligned.m8n8.x4.trans.shared.b16 {%0,%1,%2,%3}, [%4];"
                 : "=r"(r[0]), "=r"(r[1]), "=r"(r[2]), "=r"(r[3]) : "r"(addr) : "memory");
}
__device__ __forceinline__ void mma16816(float (&c)[4], const uint32_t (&a)[4], uint32_t b0, uint32_t b1) {
    asm volatile("mma.sync.aligned.m16n8k16.row.col.f32.bf16.bf16.f32 {%0,%1,%2,%3}, {%4,%5,%6,%7}, {%8,%9}, {%0,%1,%2,%3};"
                 : "+f"(c[0]), "+f"(c[1]), "+f"(c[2]), "+f"(c[3])
                 : "r"(a[0]), "r"(a[1]), "r"(a[2]), "r"(a[3]), "r"(b0), "r"(b1));
}
__device__ __forceinline__ uint32_t pack_bf16(float lo, float hi) {
    uint32_t d;
    asm("cvt.rn.bf16x2.f32 %0, %1, %2;" : "=r"(d) : "f"(hi), "f"(lo));
    return d;
}
__device__ __forceinline__ float ex2(float x) {
    float y;
    asm("ex2.approx.ftz.f32 %0, %1;" : "=f"(y) : "f"(x));
    return y;
}
__device__ __forceinline__ float rcp(float x) {
    float y;
    asm("rcp.approx.ftz.f32 %0, %1;" : "=f"(y) : "f"(x));
    return y;
}
__device__ __forceinline__ float lg2(float x) {
    float y;
    asm("lg2.approx.ftz.f32 %0, %1;" : "=f"(y) : "f"(x));
    return y;
}
__device__ __forceinline__ void lds64(uint32_t (&v)[2], uint32_t addr) {
    asm volatile("ld.shared.v2.u32 {%0, %1}, [%2];" : "=r"(v[0]), "=r"(v[1]) : "r"(addr) : "memory");
}
__device__ __forceinline__ float4 lds128f(uint32_t addr) {
    float4 v;
    asm volatile("ld.shared.v4.f32 {%0, %1, %2, %3}, [%4];" : "=f"(v.x), "=f"(v.y), "=f"(v.z), "=f"(v.w) : "r"(addr) : "memory");
    return v;
}
__device__ __forceinline__ void sts32f(uint32_t addr, float v) {
    asm volatile("st.shared.f32 [%0], %1;" ::"r"(addr), "f"(v) : "memory");
}
__device__ __forceinline__ uint32_t lds32(uint32_t addr) {
    uint32_t v;
    asm volatile("ld.shared.u32 %0, [%1];" : "=r"(v) : "r"(addr) : "memory");
    return v;
}

__device__ __forceinline__ void st_ll8(void* p, uint32_t a, uint32_t tag) {
    asm volatile("{\n.reg .b64 v;\nmov.b64 v, {%1, %2};\nst.relaxed.gpu.global.b64 [%0], v;\n}" ::"l"(p), "r"(a), "r"(tag) : "memory");
}
__device__ __forceinline__ void st_ll16(void* p, uint32_t a, uint32_t b, uint32_t c, uint32_t d) {
    asm volatile("{\n.reg .b128 v;\nmov.b128 v, {%1, %2, %3, %4};\nst.relaxed.gpu.global.b128 [%0], v;\n}"
                 ::"l"(p), "r"(a), "r"(b), "r"(c), "r"(d) : "memory");
}
__device__ __forceinline__ uint4 ld_ll16(const void* p) {
    uint4 r;
    asm volatile("{\n.reg .b128 v;\nld.relaxed.gpu.global.b128 v, [%4];\nmov.b128 {%0, %1, %2, %3}, v;\n}"
                 : "=r"(r.x), "=r"(r.y), "=r"(r.z), "=r"(r.w) : "l"(p) : "memory");
    return r;
}
__device__ __forceinline__ uint4 ld_ll8x2(const void* p) {
    unsigned long long a, b;
    asm volatile("ld.relaxed.gpu.global.v2.b64 {%0, %1}, [%2];" : "=l"(a), "=l"(b) : "l"(p) : "memory");
    return make_uint4((uint32_t)a, (uint32_t)(a >> 32), (uint32_t)b, (uint32_t)(b >> 32));
}


__global__ void __cluster_dims__(8, 1, 1) __launch_bounds__(NTHREADS, 1)
decode_kernel(
              const Params prm,
              const __grid_constant__ CUtensorMap tmKA, const __grid_constant__ CUtensorMap tmVA,
              const __grid_constant__ CUtensorMap tmKB, const __grid_constant__ CUtensorMap tmVB,
              const __grid_constant__ CUtensorMap tmWqA, const __grid_constant__ CUtensorMap tmWqB,
              const __grid_constant__ CUtensorMap tmWoA, const __grid_constant__ CUtensorMap tmWoB
              )
{
    using L = Smem;
    static_assert(IW0 == NKV && IW1 == NI - 1 && WIN < S && WIN_WO < S && IEV < NKV, "bad options");
    extern __shared__ char smem_raw[];
    const uint32_t base = (smem_u32(smem_raw) + 1023u) & ~1023u;
    char* sm = smem_raw + (base - smem_u32(smem_raw));
    const uint32_t fullb = base + L::bars, emptyb = fullb + 8 * S, xb = emptyb + 8 * S;
    const uint32_t obsbar = xb + 8 * NWB, fbar = obsbar + 8, qbar = obsbar + 16, pbar = obsbar + 24;
    volatile uint32_t* const flags = reinterpret_cast<volatile uint32_t*>(sm + L::flg);

    const int tid = threadIdx.x, warp = tid >> 5, lane = tid & 31;
    const int j = blockIdx.x;
    const bool helper = j >= NMAIN;
    const int hkv = (j >> 3) & 7, c = j & 7;
    const int bq = c >> 2, r = c & 3;

    {
        const char* w = reinterpret_cast<const char*>(prm.wqB) + (j & 63) * 128 + (helper ? 224 * 8192 : 0);
        asm volatile("prefetch.global.L2 [%0];" ::"l"(w + (size_t)tid * 8192) : "memory");
    }
    uint32_t tag;
    asm volatile("ld.relaxed.gpu.global.u32 %0, [%1];" : "=r"(tag) : "l"(prm.epoch) : "memory");
    if (warp == 4) {
        uint64_t pol = 0;
        auto issue = [&](int i, int slot) {
            const uint32_t bar = fullb + 8 * slot, dst = base + L::ring + slot * SLOT;
            if (i == IW0 || i == IW1) {
                mbar_expect_tx(bar, WO_BYTES);
                tma3d(dst, &tmWoA, 0, 0, j * 64 + (i == IW1 ? 32 : 0), bar, pol);
                return;
            }
            const int kv = i - (i > IW0) - (i > IW1);
            if (kv < NWQ) {
                mbar_expect_tx(bar, WQ_BYTES + (kv == 0 ? 2 * X_BYTES : 0));
                tma2d(dst, kv < 2 ? &tmWqB : &tmWqA, j * 64, (kv & 1) * 224, bar, pol);
                if (kv == 0) {
                    bulk1d(base + L::xs + X_BYTES, prm.xB, X_BYTES, bar);
                    bulk1d(base + L::xs, prm.xA, X_BYTES, bar);
                }
            } else {
                const int k = kv - NWQ, t = k >> 1, isV = k & 1;
                int row; const CUtensorMap* tm;
                if (t < NT_B) {
                    row = (bq * 8 + hkv) * 8192 + 6144 + (r * NT_B + t) * 64;
                    tm = isV ? &tmVB : &tmKB;
                } else {
                    row = (bq * 8 + hkv) * 8192 + (r * NT_A + t - NT_B) * 64;
                    tm = isV ? &tmVA : &tmKA;
                }
                mbar_expect_tx(bar, SLOT);
                tma3d(dst, tm, 0, row, 0, bar, pol);
            }
        };
        if (lane == 0) {
            for (int s = 0; s < S; s++) { mbar_init(fullb + 8 * s, 1); mbar_init(emptyb + 8 * s, 4); }
            for (int b = 0; b < NWB + 5; b++) mbar_init(xb + 8 * b, 1);
            mbar_expect_tx(fbar, 4096);
            mbar_expect_tx(qbar, 2048);
            mbar_expect_tx(pbar, 2112);
            mbar_expect_tx(pbar + 8, 2112);
            flags[0] = 0; flags[1] = PACE / NMAIN; flags[2] = 0; flags[3] = 0;
            asm volatile("fence.mbarrier_init.release.cluster;" ::: "memory");
            asm volatile("createpolicy.fractional.L2::evict_first.b64 %0, 1.0;" : "=l"(pol));
            if (!helper) {
                #pragma unroll 1
                for (int i = 0; i < WIN; i++) {
                    issue(i, i);
                    if (i == 1) prefetch_map(&tmWqA);
                    if (i == 3) { prefetch_map(&tmKB); prefetch_map(&tmVB); }
                }
                prefetch_map(&tmKA); prefetch_map(&tmVA); prefetch_map(&tmWoA);
            } else {
                prefetch_map(&tmWoB);
                st_ll8(prm.hello + (j - NMAIN), 0, tag + 1);
            }
        }
        start_sync();
        if (lane == 0 && !helper) {
            int slot = WIN; uint32_t ph = 1;
            bool evs = false;
            #pragma unroll 1
            for (int i = WIN; i < NI; i++) {
                const int k = i - (i >= IW0 ? WIN_WO : WIN);
                mbar_wait(fullb + 8 * (k % S), (k / S) & 1);
                if (!evs && k >= IEV) { asm volatile("red.relaxed.gpu.global.add.u32 [%0], 1;" ::"l"(prm.epoch + 64) : "memory"); evs = true; }
                mbar_wait(emptyb + 8 * slot, ph);
                const int kv = i - (i > IW0) - (i > IW1);
                const bool paced = kv >= NWQ + 2 * NT_B && i != IW0 && i != IW1;
                if (paced) {
                    const uint32_t ia = (uint32_t)(kv - (NWQ + 2 * NT_B));
                    if (flags[1] < ia) {
                        const long long t0 = clock64();
                        while (flags[1] < ia) if (clock64() - t0 > SPIN_LIMIT) __trap();
                    }
                }
                issue(i, slot);
                if (paced) asm volatile("red.relaxed.gpu.global.add.u32 [%0], 1;" ::"l"(prm.epoch + 32) : "memory");
                if (++slot == S) { slot = 0; ph ^= 1; }
            }
            flags[0] = 1;
            if (!evs) {
                mbar_wait(fullb + 8 * (IEV % S), (IEV / S) & 1);
                asm volatile("red.relaxed.gpu.global.add.u32 [%0], 1;" ::"l"(prm.epoch + 64) : "memory");
            }
        }
        if (lane == 0 && helper) {
            const uint32_t thr = REL0 + (uint32_t)(j - NMAIN) * REL1 / NHELP;
            const long long t0 = clock64();
            for (;;) {
                uint32_t v;
                asm volatile("ld.relaxed.gpu.global.u32 %0, [%1];" : "=r"(v) : "l"(prm.epoch + 64) : "memory");
                if (v - tag * NMAIN >= thr) break;
                __nanosleep(40);
                if (clock64() - t0 > SPIN_LIMIT) __trap();
            }
            #pragma unroll 1
            for (int b = 0; b < NWB; b++) {
                mbar_expect_tx(xb + 8 * b, 8192);
                tma2d(base + L::ring + b * 8192, &tmWoB, hkv * 64, c * 512 + b * 64, xb + 8 * b, pol);
            }
        }
        return;
    }
    if (warp == 5) {
        start_sync();
        if (lane == 0 && !helper) {
            const long long t0 = clock64();
            while (flags[0] == 0) {
                uint32_t v;
                asm volatile("ld.relaxed.gpu.global.u32 %0, [%1];" : "=r"(v) : "l"(prm.epoch + 32) : "memory");
                flags[1] = (v - tag * (NMAIN * 2 * NT_A) + PACE) / NMAIN;
                __nanosleep(20);
                if (clock64() - t0 > SPIN_LIMIT) __trap();
            }
        }
        return;
    }
    if (warp == 6) {
        uint2* pubob = prm.ob + j * 32 + (lane & 15) * 2 + (lane >> 4);
        if (!helper) { st_ll8(pubob, 0, 0); st_ll8(pubob + 2048, 0, 0); }
        start_sync();
        tag += 1;
        if (!helper) {
            if (j == 0) {
                for (uint32_t it = 0;; it++) {
                    uint4 v = make_uint4(0, tag, 0, tag);
                    if (lane < NHELP / 2) v = ld_ll8x2(prm.hello + lane * 2);
                    if (__all_sync(0xffffffffu, v.y == tag && v.w == tag)) break;
                    __nanosleep(100);
                    if (it > POLL_LIMIT) __trap();
                }
                if (lane == 0) flags[3] = 1;
            }
            mbar_wait_cluster(pbar + 8, 0);
            const uint32_t pb = base + L::part + PSZ;
            const bool hi = lane >= 16;
            #pragma unroll 1
            for (int b = 0; b < 2; b++) {
                const float4 a0 = lds128f(pb + b * PBS + (lane >> 4) * 512 + (lane & 15) * 16);
                const float4 a1 = lds128f(pb + b * PBS + (lane >> 4) * 512 + 256 + (lane & 15) * 16);
                const float4 m0 = lds128f(pb + 2 * PBS + b * 32), m1 = lds128f(pb + 2 * PBS + b * 32 + 16);
                const float M = fmaxf(fmaxf(m0.x, m0.z), fmaxf(m1.x, m1.z));
                const float w0 = ex2(m0.x - M), w1 = ex2(m0.z - M), w2 = ex2(m1.x - M), w3 = ex2(m1.z - M);
                const float inv = rcp(fmaf(w1, m0.w, w0 * m0.y) + fmaf(w3, m1.w, w2 * m1.y));
                const float wa = hi ? w2 : w0, wb = hi ? w3 : w1;
                const float o0 = fmaf(wb, a1.x, wa * a0.x), o1 = fmaf(wb, a1.y, wa * a0.y);
                const float o2 = fmaf(wb, a1.z, wa * a0.z), o3 = fmaf(wb, a1.w, wa * a0.w);
                const float r0 = __shfl_xor_sync(0xffffffffu, hi ? o0 : o2, 16), r1 = __shfl_xor_sync(0xffffffffu, hi ? o1 : o3, 16);
                st_ll8(pubob + b * 2048, pack_bf16(((hi ? o2 : o0) + r0) * inv, ((hi ? o3 : o1) + r1) * inv), tag);
            }
        } else {
            const uint2* src = prm.ob + c * 256 + lane * 2;
            uint4 v[8];
            #pragma unroll
            for (int i = 0; i < 8; i++) v[i] = ld_ll8x2(src + (i >> 2) * 2048 + (i & 3) * 64);
            for (uint32_t it = 0;; it++) {
                uint32_t bad = 0;
                #pragma unroll
                for (int i = 0; i < 8; i++) bad |= (v[i].y ^ tag) | (v[i].w ^ tag);
                if (__all_sync(0xffffffffu, bad == 0)) break;
                __nanosleep(400);
                #pragma unroll
                for (int i = 0; i < 8; i++)
                    if (v[i].y != tag || v[i].w != tag) v[i] = ld_ll8x2(src + (i >> 2) * 2048 + (i & 3) * 64);
                if (it > POLL_LIMIT) __trap();
            }
            #pragma unroll
            for (int i = 0; i < 8; i++)
                *reinterpret_cast<uint2*>(sm + L::obs + (i >> 2) * OBS + ((i & 3) * 32 + lane) * 8) = make_uint2(v[i].x, v[i].z);
            __syncwarp();
            if (lane == 0) mbar_arrive(obsbar);
        }
        return;
    }
    const int g = lane >> 2, t4 = lane & 3;
    const uint32_t l7 = lane & 7;
    const uint32_t offT = (l7 + (lane >> 4) * 8) * 128 + ((((lane >> 3) & 1) ^ l7) << 4);
    const uint32_t offP = (l7 + ((lane >> 3) & 1) * 8) * 128 + (((lane >> 4) ^ l7) << 4);

    if (helper) {
        __nv_bfloat16* fout = prm.out + ((lane >> 3) & 1) * 896 + 448 + hkv * 64 + warp * 16 + (lane & 7) + (lane >> 4) * 8;
        pin(fout);
        start_sync();
        const uint32_t fdst = mapa(base + L::fb + (c * 4 + warp) * 128 + g * 16, 0), fb0 = mapa(fbar, 0);
        asm volatile("barrier.cluster.wait.acquire.aligned;" ::: "memory");
        uint32_t of[NWB][4][2];
        mbar_wait(obsbar, 0);
        {
            const uint32_t oa = base + L::obs + (g & 1) * OBS + t4 * 8;
            #pragma unroll
            for (int b = 0; b < NWB; b++)
                #pragma unroll
                for (int i = 0; i < 4; i++) lds64(of[b][i], oa + b * 128 + i * 32);
        }
        const uint32_t wa = base + L::ring + (offT ^ (warp << 5));
        float acc[4][4];
        #pragma unroll
        for (int i = 0; i < 4; i++) { acc[i][0] = 0.f; acc[i][1] = 0.f; acc[i][2] = 0.f; acc[i][3] = 0.f; }
        uint32_t a[2][4][4];
        #pragma unroll
        for (int b = 0; b <= NWB; b++) {
            if (b < NWB) {
                mbar_wait(xb + 8 * b, 0);
                #pragma unroll
                for (int i = 0; i < 4; i++) ldsm4t(a[b & 1][i], wa + b * 8192 + i * 2048);
            }
            if (b > 0) {
                #pragma unroll
                for (int i = 0; i < 4; i++) mma16816(acc[i], a[(b - 1) & 1][i], of[b - 1][i][0], of[b - 1][i][1]);
            }
        }
        const float e0 = (acc[0][0] + acc[1][0]) + (acc[2][0] + acc[3][0]), e1 = (acc[0][1] + acc[1][1]) + (acc[2][1] + acc[3][1]);
        const float e2 = (acc[0][2] + acc[1][2]) + (acc[2][2] + acc[3][2]), e3 = (acc[0][3] + acc[1][3]) + (acc[2][3] + acc[3][3]);
        if (t4 == 0) st_async16(fdst, __float_as_uint(e0), __float_as_uint(e1), __float_as_uint(e2), __float_as_uint(e3), fb0);
        if (c == 0) {
            mbar_wait_cluster(fbar, 0);
            const float* fb = reinterpret_cast<const float*>(sm + L::fb) + warp * 32 + (lane & 7) * 4 + (lane >> 3);
            const float v = ((fb[0] + fb[128]) + (fb[256] + fb[384])) + ((fb[512] + fb[640]) + (fb[768] + fb[896]));
            *fout = __float2bfloat16_rn(v);
        }
        return;
    }

    constexpr int OB = 64 * 4;
    uint4* pubo = prm.outp + (((t4 * 4 + warp) * 2 + (g >> 2)) * 64 + j) * 4 + (g & 3);
    const uint4* fsrc = prm.outp + j * OB + warp * 64 + lane;
    __nv_bfloat16* fout = prm.out + ((tid >> 2) & 1) * 896 + (j >> 1) * 16 + (j & 1) * 4 + (tid & 3) + (tid & 8);
    unsigned* epoch = prm.epoch;
    pin(pubo); pin(fsrc); pin(fout); pin(epoch);
    st_ll16(pubo, 0, 0, 0, 0);
    if (t4 < 3) st_ll16(pubo + 32 * OB, 0, 0, 0, 0);
    start_sync();
    tag += 1;
    uint32_t tg = 1 + tag % TM;
    asm volatile("" : "+r"(tg));

    int slot = 0, pos = 0; uint32_t ph = 0;
    auto advance = [&]() {
        ++pos; if (++slot == S) { slot = 0; ph ^= 1; }
        if (pos == IW0) { ++pos; if (++slot == S) { slot = 0; ph ^= 1; } }
        if (pos == IW1) { ++pos; if (++slot == S) { slot = 0; ph ^= 1; } }
    };
    auto release = [&]() { __syncwarp(); if (lane == 0) mbar_arrive(emptyb + 8 * slot); };

    {
        const uint32_t rk = (lane & 1) * 4 + ((lane >> 2) & 3);
        const uint32_t qd = mapa(base + L::qs + (c * 64 + warp * 16 + ((lane >> 1) & 1) * 8) * 2, rk), qb = mapa(qbar, rk);
        #pragma unroll
        for (int pi = 0; pi < 2; pi++) {
            const int p = 1 - pi;
            float c0[4] = {0.f, 0.f, 0.f, 0.f}, c1[4] = {0.f, 0.f, 0.f, 0.f};
            const uint32_t xa = base + L::xs + p * X_BYTES + (g & 1) * 896 + t4 * 4;
            #pragma unroll
            for (int h = 0; h < 2; h++) {
                mbar_wait(fullb + 8 * slot, ph);
                const uint32_t tb = base + L::ring + slot * SLOT + (offT ^ (warp << 5));
                #pragma unroll
                for (int ks = 0; ks < 14; ks++) {
                    uint32_t a[4];
                    ldsm4t(a, tb + ks * 2048);
                    const uint32_t b0 = lds32(xa + (h * 14 + ks) * 32), b1 = lds32(xa + (h * 14 + ks) * 32 + 16);
                    if (ks & 1) mma16816(c1, a, b0, b1); else mma16816(c0, a, b0, b1);
                }
                release();
                advance();
            }
            const float lo = (t4 & 1) ? c0[1] + c1[1] : c0[0] + c1[0], hi = (t4 & 1) ? c0[3] + c1[3] : c0[2] + c1[2];
            const float v = (t4 & 2) ? hi : lo;
            const uint32_t pk = pack_bf16(v, __shfl_xor_sync(0xffffffffu, v, 4));
            const uint32_t w0 = __shfl_sync(0xffffffffu, pk, t4), w1 = __shfl_sync(0xffffffffu, pk, 8 + t4);
            const uint32_t w2 = __shfl_sync(0xffffffffu, pk, 16 + t4), w3 = __shfl_sync(0xffffffffu, pk, 24 + t4);
            if (pi == 0) asm volatile("barrier.cluster.wait.acquire.aligned;" ::: "memory");
            if (lane < 16) st_async16(qd + p * 1024, w0, w1, w2, w3, qb);
        }
        mbar_wait_cluster(qbar, 0);
    }

    constexpr float CS = 1.4426950408889634f / 16.0f;
    const uint32_t scw = base + L::sc + ((t4 & 1) * SCS + warp * 16 + (g >> 1) * 4 + (t4 >> 1) * 2 + (g & 1)) * 4;
    const uint32_t scr = base + L::sc + ((g & 1) * SCS + t4 * 4) * 4;
    const uint32_t prk = (g & 1) * 4 + warp;
    const uint32_t pdst = mapa(base + L::part + bq * PBS + r * 256 + (t4 * 4 + (g >> 1)) * 16, prk);
    const uint32_t pdml = mapa(base + L::part + 2 * PBS + (bq * 4 + r) * 8, prk), pdb = mapa(pbar, prk);
    uint32_t wa[7], mpa, mma_;
    auto addrs = [&]() {
        const uint32_t row = l7 + (lane >> 4) * 8, u = warp * 2 + ((lane >> 3) & 1);
        #pragma unroll
        for (int ch = 0; ch < 7; ch++) {
            wa[ch] = base + L::ring + row * 896 + ch * 128 + ((u ^ ((ch - row) & 7)) << 4);
        }
        mpa = base + L::part + (g & 1) * PBS + ((g >> 1) * 4 + t4) * 16;
        mma_ = base + L::part + 2 * PBS + (g & 1) * 32;
    };
    #pragma unroll 1
    for (int pi = 0; pi < 2; pi++) {
        const int p = 1 - pi;
        const int ntiles = p ? NT_B : NT_A;
        uint32_t qf[16][2];
        {
            const uint32_t qa = base + L::qs + p * 1024 + (g & 1) * 512 + t4 * 4;
            #pragma unroll
            for (int ks = 0; ks < 16; ks++) {
                qf[ks][0] = lds32(qa + ks * 32);
                qf[ks][1] = lds32(qa + ks * 32 + 16);
            }
        }
        float o[4][4], ls[4] = {0.f, 0.f, 0.f, 0.f};
        #pragma unroll
        for (int i = 0; i < 4; i++) { o[i][0] = 0.f; o[i][1] = 0.f; o[i][2] = 0.f; o[i][3] = 0.f; }
        float m = -INFINITY;
        const bool h1 = g & 1;

        #pragma unroll 1
        for (int t = 0; t < ntiles; t++) {
            mbar_wait(fullb + 8 * slot, ph);
            float sa[4] = {0.f, 0.f, 0.f, 0.f}, sb[4] = {0.f, 0.f, 0.f, 0.f};
            {
                const uint32_t kb = base + L::ring + slot * SLOT + warp * 2048;
                #pragma unroll
                for (int ks = 0; ks < 16; ks++) {
                    uint32_t a[4];
                    ldsm4(a, kb + (ks >> 2) * 8192 + (offP ^ ((ks & 3) << 5)));
                    if (ks & 1) mma16816(sb, a, qf[ks][0], qf[ks][1]); else mma16816(sa, a, qf[ks][0], qf[ks][1]);
                }
            }
            release();
            advance();
            {
                const float lo = (t4 & 1) ? sa[1] + sb[1] : sa[0] + sb[0], hi = (t4 & 1) ? sa[3] + sb[3] : sa[2] + sb[2];
                sts32f(scw + (t & 1) * (2 * SCS * 4), (t4 & 2) ? hi : lo);
            }
            cons_sync();
            float4 x[4];
            #pragma unroll
            for (int kk = 0; kk < 4; kk++) x[kk] = lds128f(scr + (t & 1) * (2 * SCS * 4) + kk * 64);
            float mx = fmaxf(fmaxf(fmaxf(x[0].x, x[0].y), fmaxf(x[0].z, x[0].w)), fmaxf(fmaxf(x[1].x, x[1].y), fmaxf(x[1].z, x[1].w)));
            mx = fmaxf(mx, fmaxf(fmaxf(fmaxf(x[2].x, x[2].y), fmaxf(x[2].z, x[2].w)), fmaxf(fmaxf(x[3].x, x[3].y), fmaxf(x[3].z, x[3].w))));
            mx = fmaxf(mx, __shfl_xor_sync(0xffffffffu, mx, 1));
            mx = fmaxf(mx, __shfl_xor_sync(0xffffffffu, mx, 2));
            if (__any_sync(0xffffffffu, mx > m)) {
                const float n = fmaxf(m, mx);
                const float f = ex2((m - n) * CS), fo = __shfl_xor_sync(0xffffffffu, f, 4);
                const float f0 = h1 ? fo : f, f1 = h1 ? f : fo;
                m = n;
                ls[0] *= f0; ls[1] *= f1;
                #pragma unroll
                for (int i = 0; i < 4; i++) { o[i][0] *= f0; o[i][1] *= f1; o[i][2] *= f0; o[i][3] *= f1; }
            }
            const float mc = m * CS;
            uint32_t pb[4][2];
            #pragma unroll
            for (int kk = 0; kk < 4; kk++) {
                pb[kk][0] = pack_bf16(ex2(fmaf(x[kk].x, CS, -mc)), ex2(fmaf(x[kk].y, CS, -mc)));
                pb[kk][1] = pack_bf16(ex2(fmaf(x[kk].z, CS, -mc)), ex2(fmaf(x[kk].w, CS, -mc)));
                const uint32_t ones[4] = {0x3F803F80u, 0x3F803F80u, 0x3F803F80u, 0x3F803F80u};
                mma16816(ls, ones, pb[kk][0], pb[kk][1]);
            }
            mbar_wait(fullb + 8 * slot, ph);
            {
                const uint32_t vb = base + L::ring + slot * SLOT + warp * 8192;
                #pragma unroll
                for (int kk = 0; kk < 4; kk++)
                    #pragma unroll
                    for (int a4 = 0; a4 < 4; a4++) {
                        uint32_t a[4];
                        ldsm4t(a, vb + kk * 2048 + (offT ^ (a4 << 5)));
                        mma16816(o[a4], a, pb[kk][0], pb[kk][1]);
                    }
            }
            release();
            advance();
        }

        {
            float v[4];
            #pragma unroll
            for (int i = 0; i < 4; i++) {
                const float a = (t4 & 1) ? o[1][i] : o[0][i], b = (t4 & 1) ? o[3][i] : o[2][i];
                v[i] = (t4 & 2) ? b : a;
            }
            const float ka = h1 ? v[1] : v[0], kb = h1 ? v[3] : v[2];
            const float ra = __shfl_xor_sync(0xffffffffu, h1 ? v[0] : v[1], 4), rb = __shfl_xor_sync(0xffffffffu, h1 ? v[2] : v[3], 4);
            st_async16(pdst + p * PSZ, __float_as_uint(h1 ? ra : ka), __float_as_uint(h1 ? ka : ra),
                       __float_as_uint(h1 ? rb : kb), __float_as_uint(h1 ? kb : rb), pdb + p * 8);
            if (lane == 0 || lane == 4) st_async8(pdml + p * PSZ, __float_as_uint(m * CS), __float_as_uint(h1 ? ls[1] : ls[0]), pdb + p * 8);
        }
    }

    {
        uint32_t wf[4][7][4];
        {
            addrs();
            bool l0 = false, l1 = false;
            auto ld0 = [&]() {
                #pragma unroll
                for (int ks = 0; ks < 2; ks++)
                    #pragma unroll
                    for (int ch = 0; ch < 7; ch++) ldsm4t(wf[ks][ch], wa[ch] + (IW0 % S) * SLOT + ks * 14336);
                l0 = true;
            };
            auto ld1 = [&]() {
                #pragma unroll
                for (int ks = 0; ks < 2; ks++)
                    #pragma unroll
                    for (int ch = 0; ch < 7; ch++) ldsm4t(wf[2 + ks][ch], wa[ch] + (IW1 % S) * SLOT + ks * 14336);
                l1 = true;
            };
            const long long tc0 = clock64();
            for (;;) {
                if (!l0) {
                    if (mbar_test(fullb + 8 * (IW0 % S), (IW0 / S) & 1)) { ld0(); }
                    if (l0 && mbar_test(fullb + 8 * (IW1 % S), (IW1 / S) & 1)) { ld1(); }
                } else if (!l1 && mbar_test(fullb + 8 * (IW1 % S), (IW1 / S) & 1)) { ld1(); }
                if (mbar_test_cluster(pbar, 0)) break;
                if (clock64() - tc0 > SPIN_LIMIT) __trap();
            }
            uint32_t of[4][2];
            {
                const uint32_t pa = mpa, ma = mma_;
                const float4 m0 = lds128f(ma), m1 = lds128f(ma + 16);
                const float4 a0 = lds128f(pa), a1 = lds128f(pa + 256), a2 = lds128f(pa + 512), a3 = lds128f(pa + 768);
                const float M = fmaxf(fmaxf(m0.x, m0.z), fmaxf(m1.x, m1.z));
                const float w0 = ex2(m0.x - M), w1 = ex2(m0.z - M), w2 = ex2(m1.x - M), w3 = ex2(m1.z - M);
                const float inv = rcp(fmaf(w1, m0.w, w0 * m0.y) + fmaf(w3, m1.w, w2 * m1.y));
                const float o0 = fmaf(w1, a1.x, w0 * a0.x) + fmaf(w3, a3.x, w2 * a2.x), o1 = fmaf(w1, a1.y, w0 * a0.y) + fmaf(w3, a3.y, w2 * a2.y);
                const float o2 = fmaf(w1, a1.z, w0 * a0.z) + fmaf(w3, a3.z, w2 * a2.z), o3 = fmaf(w1, a1.w, w0 * a0.w) + fmaf(w3, a3.w, w2 * a2.w);
                const uint32_t f0 = pack_bf16(o0 * inv, o1 * inv), f1 = pack_bf16(o2 * inv, o3 * inv);
                #pragma unroll
                for (int ks = 0; ks < 4; ks++) {
                    of[ks][0] = __shfl_sync(0xffffffffu, f0, ks * 8 + l7);
                    of[ks][1] = __shfl_sync(0xffffffffu, f1, ks * 8 + l7);
                }
            }
            float acc[7][4];
            #pragma unroll
            for (int ch = 0; ch < 7; ch++) { acc[ch][0] = 0.f; acc[ch][1] = 0.f; acc[ch][2] = 0.f; acc[ch][3] = 0.f; }
            if (!l0) {
                mbar_wait(fullb + 8 * (IW0 % S), (IW0 / S) & 1);
                #pragma unroll
                for (int ks = 0; ks < 2; ks++)
                    #pragma unroll
                    for (int ch = 0; ch < 7; ch++) ldsm4t(wf[ks][ch], wa[ch] + (IW0 % S) * SLOT + ks * 14336);
            }
            #pragma unroll
            for (int ks = 0; ks < 2; ks++)
                #pragma unroll
                for (int ch = 0; ch < 7; ch++) mma16816(acc[ch], wf[ks][ch], of[ks][0], of[ks][1]);
            if (!l1) {
                mbar_wait(fullb + 8 * (IW1 % S), (IW1 / S) & 1);
                #pragma unroll
                for (int ks = 0; ks < 2; ks++)
                    #pragma unroll
                    for (int ch = 0; ch < 7; ch++) ldsm4t(wf[2 + ks][ch], wa[ch] + (IW1 % S) * SLOT + ks * 14336);
            }
            #pragma unroll
            for (int ks = 2; ks < 4; ks++)
                #pragma unroll
                for (int ch = 0; ch < 7; ch++) mma16816(acc[ch], wf[ks][ch], of[ks][0], of[ks][1]);
            float e[4], f[4];
            #pragma unroll
            for (int i = 0; i < 4; i++) {
                const float x = (t4 & 1) ? acc[1][i] : acc[0][i], y = (t4 & 1) ? acc[3][i] : acc[2][i];
                e[i] = (t4 & 2) ? y : x;
                const float z = (t4 & 1) ? acc[5][i] : acc[4][i];
                f[i] = (t4 & 2) ? acc[6][i] : z;
            }
            st_ll16(pubo, __float_as_uint(e[0]), __float_as_uint(e[1]), __float_as_uint(e[2]), (__float_as_uint(e[3]) & ~TM) | tg);
            if (t4 < 3)
                st_ll16(pubo + 32 * OB, __float_as_uint(f[0]), __float_as_uint(f[1]), __float_as_uint(f[2]), (__float_as_uint(f[3]) & ~TM) | tg);
        }
    }

    if (j < 56) {
        uint4 va[2];
        #pragma unroll
        for (int i = 0; i < 2; i++) va[i] = ld_ll16(fsrc + i * 32);
        for (uint32_t it = 0;; it++) {
            const uint32_t bad = ((va[0].w ^ tg) | (va[1].w ^ tg)) & TM;
            if (__all_sync(0xffffffffu, bad == 0)) break;
            #pragma unroll
            for (int i = 0; i < 2; i++)
                if ((va[i].w ^ tg) & TM) va[i] = ld_ll16(fsrc + i * 32);
            if (it > POLL_LIMIT) __trap();
        }
        const float s0 = __uint_as_float(va[0].x) + __uint_as_float(va[1].x), s1 = __uint_as_float(va[0].y) + __uint_as_float(va[1].y);
        const float s2 = __uint_as_float(va[0].z) + __uint_as_float(va[1].z);
        const float s3 = __uint_as_float(va[0].w & ~TM) + __uint_as_float(va[1].w & ~TM);
        const bool h16 = lane & 16, h8 = lane & 8;
        const float a = (h16 ? s2 : s0) + __shfl_xor_sync(0xffffffffu, h16 ? s0 : s2, 16);
        const float b = (h16 ? s3 : s1) + __shfl_xor_sync(0xffffffffu, h16 ? s1 : s3, 16);
        const float cc = (h8 ? b : a) + __shfl_xor_sync(0xffffffffu, h8 ? a : b, 8);
        float* fr = reinterpret_cast<float*>(sm + L::red);
        fr[((lane >> 3) * 4 + (lane & 3)) * 12 + warp * 2 + ((lane >> 2) & 1)] = cc;
        cons_sync();
        if (tid < 16) {
            const float4 x = reinterpret_cast<const float4*>(fr)[tid * 3], y = reinterpret_cast<const float4*>(fr)[tid * 3 + 1];
            const float v = ((x.x + x.y) + (x.z + x.w)) + ((y.x + y.y) + (y.z + y.w));
            *fout = __float2bfloat16_rn(v);
            if (j == 0 && tid == 0) {
                const long long t0 = clock64();
                while (flags[3] == 0) if (clock64() - t0 > SPIN_LIMIT) __trap();
                asm volatile("st.relaxed.gpu.global.u32 [%0], %1;" ::"l"(epoch), "r"(tag) : "memory");
            }
        }
    }
}

typedef CUresult (*EncodeFn)(CUtensorMap*, CUtensorMapDataType, cuuint32_t, void*, const cuuint64_t*, const cuuint64_t*,
                             const cuuint32_t*, const cuuint32_t*, CUtensorMapInterleave, CUtensorMapSwizzle,
                             CUtensorMapL2promotion, CUtensorMapFloatOOBfill);

inline CUtensorMap make_map(EncodeFn enc, const void* ptr, int rank, const cuuint64_t* dims, const cuuint64_t* strides, const cuuint32_t* box,
                            CUtensorMapSwizzle sw = CU_TENSOR_MAP_SWIZZLE_128B, CUtensorMapL2promotion pr = CU_TENSOR_MAP_L2_PROMOTION_NONE) {
    CUtensorMap m;
    const cuuint32_t es[3] = {1, 1, 1};
    enc(&m, CU_TENSOR_MAP_DATA_TYPE_BFLOAT16, rank, const_cast<void*>(ptr), dims, strides, box, es,
        CU_TENSOR_MAP_INTERLEAVE_NONE, sw, pr,
        CU_TENSOR_MAP_FLOAT_OOB_FILL_NONE);
    return m;
}

}

static void launch_octets(void* const* d_in, void* d_out) {
    using namespace dk8;
    void* fn = nullptr;
    cudaDriverEntryPointQueryResult qr;
    cudaGetDriverEntryPoint("cuTensorMapEncodeTiled", &fn, cudaEnableDefault, &qr);
    EncodeFn enc = (EncodeFn)fn;

    const cuuint64_t kvd[3] = {64, 131072, 4}, kvs[2] = {512, 128};
    const cuuint32_t kvb[3] = {64, 64, 4};
    const cuuint64_t wqd[2] = {4096, 448}, wqs[1] = {8192};
    const cuuint32_t wqb[2] = {64, 224};
    const cuuint64_t wod[3] = {64, 7, 4096}, wos[2] = {128, 896};
    const cuuint32_t wob[3] = {64, 7, 32};
    const CUtensorMap kA = make_map(enc, d_in[1], 3, kvd, kvs, kvb), vA = make_map(enc, d_in[2], 3, kvd, kvs, kvb);
    const CUtensorMap kB = make_map(enc, d_in[6], 3, kvd, kvs, kvb), vB = make_map(enc, d_in[7], 3, kvd, kvs, kvb);
    const CUtensorMap wqA = make_map(enc, d_in[3], 2, wqd, wqs, wqb), wqB = make_map(enc, d_in[8], 2, wqd, wqs, wqb);
    const cuuint64_t wcd[2] = {448, 4096}, wcs[1] = {896};
    const cuuint32_t wcb[2] = {64, 64};
    const CUtensorMap woA = make_map(enc, d_in[4], 3, wod, wos, wob);
    const CUtensorMap woB = make_map(enc, d_in[9], 2, wcd, wcs, wcb);
    Params prm;
    prm.xA = (const __nv_bfloat16*)d_in[0];
    prm.xB = (const __nv_bfloat16*)d_in[5];
    prm.wqA = (const __nv_bfloat16*)d_in[3];
    prm.wqB = (const __nv_bfloat16*)d_in[8];
    prm.out = (__nv_bfloat16*)d_out;
    void* a = nullptr;
    cudaGetSymbolAddress(&a, g_epoch); prm.epoch = (unsigned*)a;
    cudaGetSymbolAddress(&a, g_out);   prm.outp = (uint4*)a;
    cudaGetSymbolAddress(&a, g_ob);    prm.ob = (uint2*)a;
    cudaGetSymbolAddress(&a, g_hello); prm.hello = (uint2*)a;

    cudaFuncSetAttribute(decode_kernel, cudaFuncAttributeMaxDynamicSharedMemorySize, Smem::total);
    decode_kernel<<<NCTA, NTHREADS, Smem::total>>>(prm, kA, vA, kB, vB, wqA, wqB, woA, woB);
}

namespace dk2 {

constexpr int NCTA     = 128;
constexpr int NTHREADS = 224;
constexpr int S        = 6;
constexpr int SLOT     = 32768;
constexpr int NT_B     = 4;
constexpr int NT_A     = 16;
constexpr int NKV      = 2 + 2 * (NT_A + NT_B);
constexpr int WQ_BYTES = 224 * 128;
constexpr int X_BYTES  = 2 * 448 * 2;
constexpr int NWO      = 8;
constexpr int RBA      = 8;
constexpr int RBB      = 256;
constexpr int WIN      = 5;
constexpr int WIN0     = 3;
constexpr int N0       = 6;
constexpr int WA       = 2;
constexpr int WB       = 4;
constexpr int TH       = 32;
constexpr uint32_t TM  = 7;
constexpr int OBS      = 4096 + 32;
constexpr int OSS      = 128 + 32;
constexpr int SCS      = 80;
constexpr long long SPIN_LIMIT = 4000000000LL;

struct Smem {
    static constexpr int ring = 0;
    static constexpr int red  = S * SLOT;
    static constexpr int sc   = red + 1024;
    static constexpr int flg  = sc + 4 * SCS * 4;
    static constexpr int xs   = flg + 128;
    static constexpr int qs   = xs + X_BYTES;
    static constexpr int os   = qs + 2048;
    static constexpr int obs  = os + 2 * OSS;
    static constexpr int fb   = obs + 2 * OBS;
    static constexpr int bars = fb + 1024;
    static constexpr int total = bars + 16 * S + 128 + 1024;
};

struct Params {
    const __nv_bfloat16* xA;
    const __nv_bfloat16* xB;
    const __nv_bfloat16* wqA;
    const __nv_bfloat16* wqB;
    const __nv_bfloat16* kB;
    const __nv_bfloat16* vB;
    const __nv_bfloat16* kA;
    const __nv_bfloat16* vA;
    __nv_bfloat16* out;
    unsigned* epoch;
    uint2* q;
    uint4* part;
    uint4* outp;
    uint2* ob;
};

__device__ __align__(128) unsigned g_epoch[64];
__device__ __align__(128) uint2 g_q[2][2][2048];
__device__ __align__(128) uint4 g_part[2][16][4][2][8][16];
__device__ __align__(128) uint4 g_out[56][64][4];
__device__ __align__(128) uint2 g_ob[2][2048];

__device__ __forceinline__ uint32_t smem_u32(const void* p) { return (uint32_t)__cvta_generic_to_shared(p); }
__device__ __forceinline__ void mbar_init(uint32_t bar, uint32_t cnt) {
    asm volatile("mbarrier.init.shared::cta.b64 [%0], %1;" ::"r"(bar), "r"(cnt) : "memory");
}
__device__ __forceinline__ void mbar_expect_tx(uint32_t bar, uint32_t bytes) {
    asm volatile("mbarrier.arrive.expect_tx.shared::cta.b64 _, [%0], %1;" ::"r"(bar), "r"(bytes) : "memory");
}
__device__ __forceinline__ void mbar_arrive(uint32_t bar) {
    asm volatile("mbarrier.arrive.shared::cta.b64 _, [%0];" ::"r"(bar) : "memory");
}
__device__ __forceinline__ bool mbar_try(uint32_t bar, uint32_t parity) {
    uint32_t ok;
    asm volatile("{\n.reg .pred p;\nmbarrier.try_wait.parity.shared::cta.b64 p, [%1], %2;\nselp.u32 %0, 1, 0, p;\n}"
                 : "=r"(ok) : "r"(bar), "r"(parity) : "memory");
    return ok != 0;
}
__device__ __forceinline__ bool mbar_test(uint32_t bar, uint32_t parity) {
    uint32_t ok;
    asm volatile("{\n.reg .pred p;\nmbarrier.test_wait.parity.shared::cta.b64 p, [%1], %2;\nselp.u32 %0, 1, 0, p;\n}"
                 : "=r"(ok) : "r"(bar), "r"(parity) : "memory");
    return __all_sync(0xffffffffu, ok != 0);
}
__device__ __forceinline__ void mbar_wait(uint32_t bar, uint32_t parity) {
    if (mbar_try(bar, parity)) return;
    const long long t0 = clock64();
    while (!mbar_try(bar, parity))
        if (clock64() - t0 > SPIN_LIMIT) __trap();
}
template <typename T> __device__ __forceinline__ void pin(T*& p) { asm volatile("" : "+l"(p)); }
constexpr uint32_t POLL_LIMIT = 1u << 24;
__device__ __forceinline__ void cons_sync() { asm volatile("bar.sync 1, 128;" ::: "memory"); }
__device__ __forceinline__ void start_sync() {
    __syncthreads();
    asm volatile("barrier.cluster.arrive.relaxed.aligned;" ::: "memory");
}
__device__ __forceinline__ uint32_t mapa0(uint32_t addr) {
    uint32_t r;
    asm("mapa.shared::cluster.u32 %0, %1, 0;" : "=r"(r) : "r"(addr));
    return r;
}
__device__ __forceinline__ void st_async16(uint32_t addr, float a, float b, float c, float d, uint32_t bar) {
    asm volatile("st.async.weak.shared::cluster.mbarrier::complete_tx::bytes.v4.f32 [%0], {%1, %2, %3, %4}, [%5];"
                 ::"r"(addr), "f"(a), "f"(b), "f"(c), "f"(d), "r"(bar) : "memory");
}
__device__ __forceinline__ void mbar_wait_cluster(uint32_t bar, uint32_t parity) {
    const long long t0 = clock64();
    for (;;) {
        uint32_t ok;
        asm volatile("{\n.reg .pred p;\nmbarrier.try_wait.parity.acquire.cluster.shared::cta.b64 p, [%1], %2;\nselp.u32 %0, 1, 0, p;\n}"
                     : "=r"(ok) : "r"(bar), "r"(parity) : "memory");
        if (ok) return;
        if (clock64() - t0 > SPIN_LIMIT) __trap();
    }
}

__device__ __forceinline__ void tma2d(uint32_t dst, const CUtensorMap* tm, int c0, int c1, uint32_t bar, uint64_t pol) {
    asm volatile("cp.async.bulk.tensor.2d.shared::cluster.global.mbarrier::complete_tx::bytes.L2::cache_hint [%0], [%1, {%3, %4}], [%2], %5;"
                 ::"r"(dst), "l"(tm), "r"(bar), "r"(c0), "r"(c1), "l"(pol) : "memory");
}
__device__ __forceinline__ void tma3d(uint32_t dst, const CUtensorMap* tm, int c0, int c1, int c2, uint32_t bar, uint64_t pol) {
    asm volatile("cp.async.bulk.tensor.3d.shared::cluster.global.mbarrier::complete_tx::bytes.L2::cache_hint [%0], [%1, {%3, %4, %5}], [%2], %6;"
                 ::"r"(dst), "l"(tm), "r"(bar), "r"(c0), "r"(c1), "r"(c2), "l"(pol) : "memory");
}
__device__ __forceinline__ void bulk1d(uint32_t dst, const void* src, uint32_t bytes, uint32_t bar) {
    asm volatile("cp.async.bulk.shared::cluster.global.mbarrier::complete_tx::bytes [%0], [%1], %2, [%3];"
                 ::"r"(dst), "l"(src), "r"(bytes), "r"(bar) : "memory");
}
__device__ __forceinline__ void prefetch_map(const CUtensorMap* tm) {
    asm volatile("prefetch.tensormap [%0];" ::"l"(tm) : "memory");
}

__device__ __forceinline__ void ldsm4(uint32_t (&r)[4], uint32_t addr) {
    asm volatile("ldmatrix.sync.aligned.m8n8.x4.shared.b16 {%0,%1,%2,%3}, [%4];"
                 : "=r"(r[0]), "=r"(r[1]), "=r"(r[2]), "=r"(r[3]) : "r"(addr) : "memory");
}
__device__ __forceinline__ void ldsm4t(uint32_t (&r)[4], uint32_t addr) {
    asm volatile("ldmatrix.sync.aligned.m8n8.x4.trans.shared.b16 {%0,%1,%2,%3}, [%4];"
                 : "=r"(r[0]), "=r"(r[1]), "=r"(r[2]), "=r"(r[3]) : "r"(addr) : "memory");
}
__device__ __forceinline__ void mma16816(float (&c)[4], const uint32_t (&a)[4], uint32_t b0, uint32_t b1) {
    asm volatile("mma.sync.aligned.m16n8k16.row.col.f32.bf16.bf16.f32 {%0,%1,%2,%3}, {%4,%5,%6,%7}, {%8,%9}, {%0,%1,%2,%3};"
                 : "+f"(c[0]), "+f"(c[1]), "+f"(c[2]), "+f"(c[3])
                 : "r"(a[0]), "r"(a[1]), "r"(a[2]), "r"(a[3]), "r"(b0), "r"(b1));
}
__device__ __forceinline__ uint32_t pack_bf16(float lo, float hi) {
    uint32_t d;
    asm("cvt.rn.bf16x2.f32 %0, %1, %2;" : "=r"(d) : "f"(hi), "f"(lo));
    return d;
}
__device__ __forceinline__ float ex2(float x) {
    float y;
    asm("ex2.approx.ftz.f32 %0, %1;" : "=f"(y) : "f"(x));
    return y;
}
__device__ __forceinline__ float rcp(float x) {
    float y;
    asm("rcp.approx.ftz.f32 %0, %1;" : "=f"(y) : "f"(x));
    return y;
}
__device__ __forceinline__ float lg2(float x) {
    float y;
    asm("lg2.approx.ftz.f32 %0, %1;" : "=f"(y) : "f"(x));
    return y;
}
__device__ __forceinline__ void lds64(uint32_t (&v)[2], uint32_t addr) {
    asm volatile("ld.shared.v2.u32 {%0, %1}, [%2];" : "=r"(v[0]), "=r"(v[1]) : "r"(addr) : "memory");
}
__device__ __forceinline__ float4 lds128f(uint32_t addr) {
    float4 v;
    asm volatile("ld.shared.v4.f32 {%0, %1, %2, %3}, [%4];" : "=f"(v.x), "=f"(v.y), "=f"(v.z), "=f"(v.w) : "r"(addr) : "memory");
    return v;
}
__device__ __forceinline__ void sts32f(uint32_t addr, float v) {
    asm volatile("st.shared.f32 [%0], %1;" ::"r"(addr), "f"(v) : "memory");
}
__device__ __forceinline__ uint32_t lds32(uint32_t addr) {
    uint32_t v;
    asm volatile("ld.shared.u32 %0, [%1];" : "=r"(v) : "r"(addr) : "memory");
    return v;
}

__device__ __forceinline__ void st_ll8(void* p, uint32_t a, uint32_t tag) {
    asm volatile("{\n.reg .b64 v;\nmov.b64 v, {%1, %2};\nst.relaxed.gpu.global.b64 [%0], v;\n}" ::"l"(p), "r"(a), "r"(tag) : "memory");
}
__device__ __forceinline__ void st_ll16(void* p, uint32_t a, uint32_t b, uint32_t c, uint32_t d) {
    asm volatile("{\n.reg .b128 v;\nmov.b128 v, {%1, %2, %3, %4};\nst.relaxed.gpu.global.b128 [%0], v;\n}"
                 ::"l"(p), "r"(a), "r"(b), "r"(c), "r"(d) : "memory");
}
__device__ __forceinline__ uint4 ld_ll16(const void* p) {
    uint4 r;
    asm volatile("{\n.reg .b128 v;\nld.relaxed.gpu.global.b128 v, [%4];\nmov.b128 {%0, %1, %2, %3}, v;\n}"
                 : "=r"(r.x), "=r"(r.y), "=r"(r.z), "=r"(r.w) : "l"(p) : "memory");
    return r;
}
__device__ __forceinline__ uint4 ld_ll8x2(const void* p) {
    unsigned long long a, b;
    asm volatile("ld.relaxed.gpu.global.v2.b64 {%0, %1}, [%2];" : "=l"(a), "=l"(b) : "l"(p) : "memory");
    return make_uint4((uint32_t)a, (uint32_t)(a >> 32), (uint32_t)b, (uint32_t)(b >> 32));
}

__device__ __forceinline__ uint32_t merge4(const uint4 (&v)[4], int lane) {
    float l[4], w[4];
    #pragma unroll
    for (int i = 0; i < 4; i++) l[i] = __uint_as_float(v[i].w & ~TM);
    float M = fmaxf(fmaxf(l[0], l[1]), fmaxf(l[2], l[3]));
    M = fmaxf(M, __shfl_xor_sync(0xffffffffu, M, 16));
    float a[4][4];
    #pragma unroll
    for (int i = 0; i < 4; i++) {
        a[i][0] = __uint_as_float(v[i].x & 0xffffff00u);
        a[i][1] = __uint_as_float(v[i].y & 0xffffff00u);
        a[i][2] = __uint_as_float(v[i].z & 0xffffff00u);
        a[i][3] = __uint_as_float(__byte_perm(__byte_perm(v[i].y, v[i].z, 0x4000), v[i].x << 8, 0x3254));
    }
    #pragma unroll
    for (int i = 0; i < 4; i++) w[i] = ex2(l[i] - M);
    float o[4];
    #pragma unroll
    for (int d = 0; d < 4; d++) o[d] = fmaf(w[1], a[1][d], w[0] * a[0][d]) + fmaf(w[3], a[3][d], w[2] * a[2][d]);
    float sum = (w[0] + w[1]) + (w[2] + w[3]);
    const bool hi = lane >= 16;
    const float r0 = __shfl_xor_sync(0xffffffffu, hi ? o[0] : o[2], 16), r1 = __shfl_xor_sync(0xffffffffu, hi ? o[1] : o[3], 16);
    sum += __shfl_xor_sync(0xffffffffu, sum, 16);
    const float inv = rcp(sum);
    return pack_bf16(((hi ? o[2] : o[0]) + r0) * inv, ((hi ? o[3] : o[1]) + r1) * inv);
}


__global__ void __cluster_dims__(2, 1, 1) __launch_bounds__(NTHREADS, 1)
decode_kernel(const __grid_constant__ CUtensorMap tmKA, const __grid_constant__ CUtensorMap tmVA,
              const __grid_constant__ CUtensorMap tmKB, const __grid_constant__ CUtensorMap tmVB,
              const __grid_constant__ CUtensorMap tmWqA, const __grid_constant__ CUtensorMap tmWqB,
              const __grid_constant__ CUtensorMap tmWoA, const __grid_constant__ CUtensorMap tmWoB,
              const Params prm)
{
    using L = Smem;
    extern __shared__ char smem_raw[];
    const uint32_t base = (smem_u32(smem_raw) + 1023u) & ~1023u;
    char* sm = smem_raw + (base - smem_u32(smem_raw));
    const uint32_t fullb = base + L::bars, emptyb = fullb + 8 * S, wob = emptyb + 8 * S;
    volatile uint32_t* const flags = reinterpret_cast<volatile uint32_t*>(sm + L::flg);

    const int tid = threadIdx.x, warp = tid >> 5, lane = tid & 31;
    const int j = blockIdx.x;
    const int grp = j >> 3, r = j & 7;
    const int pj = j >> 6, sj = j & 63;

    {
        const char* w = reinterpret_cast<const char*>(pj ? prm.wqB : prm.wqA) + sj * 128;
        asm volatile("prefetch.global.L2 [%0];" ::"l"(w + (size_t)tid * 8192) : "memory");
    }
    uint32_t tag;
    asm volatile("ld.relaxed.gpu.global.u32 %0, [%1];" : "=r"(tag) : "l"(prm.epoch) : "memory");
    const uint4* msrc = prm.part + ((((pj * 16 + (sj >> 2)) * 4 + (sj & 3)) * 2 + (pj ? 0 : (warp - 5) & 1)) * 8 + (lane >> 4) * 4) * 16 + (lane & 15);
    pin(msrc);
    if (warp == 4) {
        const CUtensorMap* tmWq = pj ? &tmWqB : &tmWqA;
        const CUtensorMap* tmWo = pj ? &tmWoB : &tmWoA;
        uint64_t pol = 0;
        auto issue = [&](int i, int slot) {
            const uint32_t bar = fullb + 8 * slot, dst = base + L::ring + slot * SLOT;
            if (i < 2) {
                mbar_expect_tx(bar, WQ_BYTES + (i == 0 ? X_BYTES : 0));
                tma2d(dst, tmWq, sj * 64, i * 224, bar, pol);
                if (i == 0) bulk1d(base + L::xs, pj ? prm.xB : prm.xA, X_BYTES, bar);
            } else {
                const int k = i - 2, t = k >> 1, isV = k & 1;
                int row; const CUtensorMap* tm;
                if (t < NT_B) {
                    row = grp * 8192 + 6144 + (r * NT_B + t) * 64;
                    tm = isV ? &tmVB : &tmKB;
                } else {
                    row = grp * 8192 + (r * NT_A + t - NT_B) * 64;
                    tm = isV ? &tmVA : &tmKA;
                }
                mbar_expect_tx(bar, SLOT);
                tma3d(dst, tm, 0, row, 0, bar, pol);
            }
        };
        auto issue_wo = [&](int c) {
            if (pj == 0) {
                mbar_expect_tx(wob + 8 * c, RBA * 896);
                tma3d(base + L::ring + (NKV % S) * SLOT + c * RBA * 896, tmWo, 0, 0, sj * 64 + c * RBA, wob + 8 * c, pol);
            } else {
                mbar_expect_tx(wob + 8 * c, RBB * 32);
                tma2d(base + L::ring + (NKV % S) * SLOT + c * RBB * 32, tmWo, (sj >> 1) * 16, (sj & 1) * 2048 + c * RBB, wob + 8 * c, pol);
            }
        };
        if (lane == 0) {
            for (int s = 0; s < S; s++) { mbar_init(fullb + 8 * s, 1); mbar_init(emptyb + 8 * s, 4); }
            for (int c = 0; c < NWO; c++) mbar_init(wob + 8 * c, 1);
            mbar_init(wob + 8 * NWO, 2);
            mbar_init(wob + 8 * NWO + 8, 1);
            mbar_init(wob + 8 * NWO + 16, 1);
            mbar_expect_tx(wob + 8 * NWO + 16, 1024);
            flags[0] = 0; flags[1] = TH / NCTA; flags[2] = 0;
            asm volatile("fence.mbarrier_init.release.cluster;" ::: "memory");
            asm volatile("createpolicy.fractional.L2::evict_first.b64 %0, 1.0;" : "=l"(pol));
            #pragma unroll 1
            for (int i = 0; i < WIN0; i++) {
                issue(i, i);
                if (i == 1) { prefetch_map(&tmKB); prefetch_map(&tmVB); }
            }
            prefetch_map(&tmKA); prefetch_map(&tmVA); prefetch_map(tmWo);
        }
        start_sync();
        if (lane == 0) {
            int slot = WIN0; uint32_t ph = 1;
            #pragma unroll 1
            for (int i = WIN0; i < NKV; i++) {
                const int k = i - (i < N0 ? WIN0 : WIN);
                mbar_wait(fullb + 8 * (k % S), (k / S) & 1);
                mbar_wait(emptyb + 8 * slot, ph);
                const bool paced = i >= 2 + 2 * NT_B;
                if (paced) {
                    const uint32_t ia = (uint32_t)(i - (2 + 2 * NT_B));
                    if (flags[1] < ia) {
                        const long long t0 = clock64();
                        while (flags[1] < ia) if (clock64() - t0 > SPIN_LIMIT) __trap();
                    }
                }
                issue(i, slot);
                if (paced) asm volatile("red.relaxed.gpu.global.add.u32 [%0], 1;" ::"l"(prm.epoch + 32) : "memory");
                if (++slot == S) { slot = 0; ph ^= 1; }
            }
            flags[0] = 1;
            static_assert(NKV % S == 0 && NWO * RBA * 896 <= 2 * SLOT && NWO * RBB * 32 <= 2 * SLOT, "the wo slice lives in ring slots 0 and 1");
            static_assert(WIN0 < S && WIN < S && NWO * RBA == 64 && NWO * RBB == 2048, "bad options");
            if (j < 120) {
                mbar_wait(emptyb + 8 * (NKV % S), ((NKV / S) & 1) ^ 1);
                mbar_wait(emptyb + 8 * ((NKV + 1) % S), (((NKV + 1) / S) & 1) ^ 1);
                const int wa = pj ? 0 : WA, wc = pj ? WB : NWO;
                mbar_wait(fullb + 8 * ((NKV - 2) % S), ((NKV - 2) / S) & 1);
                #pragma unroll 1
                for (int c = 0; c < wa; c++) issue_wo(c);
                mbar_wait(fullb + 8 * ((NKV - 1) % S), ((NKV - 1) / S) & 1);
                #pragma unroll 1
                for (int c = wa; c < NWO; c++) {
                    if (c >= wc) mbar_wait(wob + 8 * (c - wc), 0);
                    issue_wo(c);
                }
            }
        }
        return;
    }
    if (warp == 5) {
        start_sync();
        if (lane == 0) {
            const long long t0 = clock64();
            while (flags[0] == 0) {
                uint32_t v;
                asm volatile("ld.relaxed.gpu.global.u32 %0, [%1];" : "=r"(v) : "l"(prm.epoch + 32) : "memory");
                flags[1] = (v - tag * (NCTA * 2 * NT_A) + TH) / NCTA;
                __nanosleep(20);
                if (clock64() - t0 > SPIN_LIMIT) __trap();
            }
        }
        __syncwarp();
        if (pj) return;
    }
    uint2* pubob = prm.ob + sj * 32 + (lane & 15) * 2 + (lane >> 4);
    if (warp == 6) {
        if (pj) { st_ll8(pubob, 0, 0); st_ll8(pubob + 2048, 0, 0); }
        start_sync();
    }
    if (warp == 6 && pj) {
        if (lane == 0) {
            const long long t0 = clock64();
            while (flags[2] == 0) { __nanosleep(200); if (clock64() - t0 > SPIN_LIMIT) __trap(); }
        }
        __syncwarp();
        tag += 1;
        #pragma unroll 1
        for (int b = 0; b < 2; b++) {
            const uint32_t tg = 1 + tag % TM;
            uint4 v[4];
            #pragma unroll
            for (int i = 0; i < 4; i++) v[i] = ld_ll16(msrc + (b * 8 + i) * 16);
            for (uint32_t it = 0;; it++) {
                uint32_t bad = 0;
                #pragma unroll
                for (int i = 0; i < 4; i++) bad |= (v[i].w ^ tg) & TM;
                if (__all_sync(0xffffffffu, bad == 0)) break;
                __nanosleep(200);
                #pragma unroll
                for (int i = 0; i < 4; i++)
                    if ((v[i].w ^ tg) & TM) v[i] = ld_ll16(msrc + (b * 8 + i) * 16);
                if (it > POLL_LIMIT) __trap();
            }
            const uint32_t res = merge4(v, lane);
            st_ll8(pubob + b * 2048, res, tag);
        }
        if (j < 120) {
            #pragma unroll 1
            for (int c = 0; c < 4; c++) {
                const uint2* src = prm.ob + (c >> 1) * 2048 + (j & 1) * 1024 + (c & 1) * 512 + lane * 2;
                uint4 v[8];
                #pragma unroll
                for (int i = 0; i < 8; i++) v[i] = ld_ll8x2(src + i * 64);
                for (uint32_t it = 0;; it++) {
                    uint32_t bad = 0;
                    #pragma unroll
                    for (int i = 0; i < 8; i++) bad |= (v[i].y ^ tag) | (v[i].w ^ tag);
                    if (__all_sync(0xffffffffu, bad == 0)) break;
                    __nanosleep(200);
                    #pragma unroll
                    for (int i = 0; i < 8; i++)
                        if (v[i].y != tag || v[i].w != tag) v[i] = ld_ll8x2(src + i * 64);
                    if (it > POLL_LIMIT) __trap();
                }
                uint2* dst = reinterpret_cast<uint2*>(sm + L::obs + (c >> 1) * OBS + (c & 1) * 2048) + lane;
                #pragma unroll
                for (int i = 0; i < 8; i++) dst[i * 32] = make_uint2(v[i].x, v[i].z);
            }
            __syncwarp();
            if (lane == 0) mbar_arrive(wob + 8 * NWO + 8);
        }
        return;
    }
    if (warp == 5 || warp == 6) {
        asm volatile("bar.sync 3, 64;" ::: "memory");
        mbar_wait(fullb + 8 * ((NKV - 1) % S), ((NKV - 1) / S) & 1);
        tag += 1;
        const uint32_t tg = 1 + tag % TM;
        uint4 v[4];
        #pragma unroll
        for (int i = 0; i < 4; i++) v[i] = ld_ll16(msrc + i * 16);
        for (uint32_t it = 0;; it++) {
            const uint32_t bad = (((v[0].w ^ tg) | (v[1].w ^ tg)) | ((v[2].w ^ tg) | (v[3].w ^ tg))) & TM;
            if (__all_sync(0xffffffffu, bad == 0)) break;
            #pragma unroll
            for (int i = 0; i < 4; i++)
                if ((v[i].w ^ tg) & TM) v[i] = ld_ll16(msrc + i * 16);
            if (it > POLL_LIMIT) __trap();
        }
        const uint32_t res = merge4(v, lane);
        reinterpret_cast<uint32_t*>(sm + L::os)[(warp - 5) * (OSS / 4) + (lane & 15) * 2 + (lane >> 4)] = res;
        __syncwarp();
        if (lane == 0) mbar_arrive(wob + 8 * NWO);
        return;
    }
    const int g = lane >> 2, t4 = lane & 3;
    const int bq = grp >> 3, hkv = grp & 7;
    uint2* pubq = prm.q + (pj * 2 + (t4 & 1)) * 2048 + sj * 32 + warp * 8 + (t4 >> 1) * 4 + (g >> 1);
    uint4* pubp = prm.part + ((((hkv * 2 + (g & 1)) * 4 + warp) * 2 + bq) * 8 + r) * 16 + t4 * 4 + (g >> 1);
    constexpr int PP = 16 * 4 * 2 * 8 * 16;
    constexpr int OB = 64 * 4;
    uint4* pubo = prm.outp + (((t4 * 4 + warp) * 2 + (g >> 2)) * 64 + sj) * 4 + (g & 3);
    const uint4* fsrc = prm.outp + j * OB + warp * 64 + lane;
    __nv_bfloat16* fout = pj ? prm.out + (lane >> 4) * 896 + 448 + (sj >> 1) * 16 + (lane & 15)
                             : prm.out + ((tid >> 2) & 1) * 896 + (j >> 1) * 16 + (j & 1) * 4 + (tid & 3) + (tid & 8);
    unsigned* epoch = prm.epoch;
    pin(pubp); pin(pubo); pin(fsrc); pin(fout); pin(epoch);
    if (!(g & 1)) st_ll8(pubq, 0, 0);
    st_ll16(pubp, 0, 0, 0, 0); st_ll16(pubp + PP, 0, 0, 0, 0);
    if (!pj) {
        st_ll16(pubo, 0, 0, 0, 0);
        if (t4 < 3) st_ll16(pubo + 32 * OB, 0, 0, 0, 0);
    }
    start_sync();
    tag += 1;
    uint32_t tg = 1 + tag % TM;
    asm volatile("" : "+r"(tg));

    int slot = 0; uint32_t ph = 0;
    auto advance = [&]() { if (++slot == S) { slot = 0; ph ^= 1; } };
    auto release = [&]() { __syncwarp(); if (lane == 0) mbar_arrive(emptyb + 8 * slot); };

    const uint32_t l7 = lane & 7;
    const uint32_t offT = (l7 + (lane >> 4) * 8) * 128 + ((((lane >> 3) & 1) ^ l7) << 4);
    const uint32_t offP = (l7 + ((lane >> 3) & 1) * 8) * 128 + (((lane >> 4) ^ l7) << 4);

    {
        float c0[4] = {0.f, 0.f, 0.f, 0.f}, c1[4] = {0.f, 0.f, 0.f, 0.f};
        const uint32_t xa = base + L::xs + (g & 1) * 896 + t4 * 4;
        #pragma unroll
        for (int h = 0; h < 2; h++) {
            mbar_wait(fullb + 8 * slot, ph);
            const uint32_t tb = base + L::ring + slot * SLOT + (offT ^ (warp << 5));
            #pragma unroll
            for (int ks = 0; ks < 14; ks++) {
                uint32_t a[4];
                ldsm4t(a, tb + ks * 2048);
                const uint32_t b0 = lds32(xa + (h * 14 + ks) * 32), b1 = lds32(xa + (h * 14 + ks) * 32 + 16);
                if (ks & 1) mma16816(c1, a, b0, b1); else mma16816(c0, a, b0, b1);
            }
            release();
            advance();
        }
        const float lo = (t4 & 1) ? c0[1] + c1[1] : c0[0] + c1[0], hi = (t4 & 1) ? c0[3] + c1[3] : c0[2] + c1[2];
        const float v = (t4 & 2) ? hi : lo;
        const float vn = __shfl_xor_sync(0xffffffffu, v, 4);
        if (!(g & 1)) st_ll8(pubq, pack_bf16(v, vn), tag);
    }
    {
        const uint2* s0 = prm.q + bq * 2048 + hkv * 256 + tid * 2;
        const uint2* s1 = s0 + 2 * 2048;
        uint4 v0, v1;
        v0 = ld_ll8x2(s0);
        v1 = ld_ll8x2(s1);
        for (uint32_t it = 0; !__all_sync(0xffffffffu, v0.y == tag && v0.w == tag && v1.y == tag && v1.w == tag); it++) {
            if (v0.y != tag || v0.w != tag) v0 = ld_ll8x2(s0);
            if (v1.y != tag || v1.w != tag) v1 = ld_ll8x2(s1);
            if (it > POLL_LIMIT) __trap();
        }
        uint2* qs = reinterpret_cast<uint2*>(sm + L::qs);
        qs[tid] = make_uint2(v0.x, v0.z);
        qs[128 + tid] = make_uint2(v1.x, v1.z);
        cons_sync();
    }

    constexpr float CS = 1.4426950408889634f / 16.0f;
    const uint32_t scw = base + L::sc + ((t4 & 1) * SCS + warp * 16 + (g >> 1) * 4 + (t4 >> 1) * 2 + (g & 1)) * 4;
    const uint32_t scr = base + L::sc + ((g & 1) * SCS + t4 * 4) * 4;
    #pragma unroll 1
    for (int pi = 0; pi < 2; pi++) {
        const int p = 1 - pi;
        const int ntiles = p ? NT_B : NT_A;
        uint32_t qf[16][2];
        {
            const uint32_t qa = base + L::qs + p * 1024 + (g & 1) * 512 + t4 * 4;
            #pragma unroll
            for (int ks = 0; ks < 16; ks++) {
                qf[ks][0] = lds32(qa + ks * 32);
                qf[ks][1] = lds32(qa + ks * 32 + 16);
            }
        }
        float o[4][4], ls[4] = {0.f, 0.f, 0.f, 0.f};
        #pragma unroll
        for (int i = 0; i < 4; i++) { o[i][0] = 0.f; o[i][1] = 0.f; o[i][2] = 0.f; o[i][3] = 0.f; }
        float m = -INFINITY;
        const bool h1 = g & 1;

        #pragma unroll 1
        for (int t = 0; t < ntiles; t++) {
            mbar_wait(fullb + 8 * slot, ph);
            float sa[4] = {0.f, 0.f, 0.f, 0.f}, sb[4] = {0.f, 0.f, 0.f, 0.f};
            {
                const uint32_t kb = base + L::ring + slot * SLOT + warp * 2048;
                #pragma unroll
                for (int ks = 0; ks < 16; ks++) {
                    uint32_t a[4];
                    ldsm4(a, kb + (ks >> 2) * 8192 + (offP ^ ((ks & 3) << 5)));
                    if (ks & 1) mma16816(sb, a, qf[ks][0], qf[ks][1]); else mma16816(sa, a, qf[ks][0], qf[ks][1]);
                }
            }
            release();
            advance();
            {
                const float lo = (t4 & 1) ? sa[1] + sb[1] : sa[0] + sb[0], hi = (t4 & 1) ? sa[3] + sb[3] : sa[2] + sb[2];
                sts32f(scw + (t & 1) * (2 * SCS * 4), (t4 & 2) ? hi : lo);
            }
            cons_sync();
            float4 x[4];
            #pragma unroll
            for (int kk = 0; kk < 4; kk++) x[kk] = lds128f(scr + (t & 1) * (2 * SCS * 4) + kk * 64);
            float mx = fmaxf(fmaxf(fmaxf(x[0].x, x[0].y), fmaxf(x[0].z, x[0].w)), fmaxf(fmaxf(x[1].x, x[1].y), fmaxf(x[1].z, x[1].w)));
            mx = fmaxf(mx, fmaxf(fmaxf(fmaxf(x[2].x, x[2].y), fmaxf(x[2].z, x[2].w)), fmaxf(fmaxf(x[3].x, x[3].y), fmaxf(x[3].z, x[3].w))));
            mx = fmaxf(mx, __shfl_xor_sync(0xffffffffu, mx, 1));
            mx = fmaxf(mx, __shfl_xor_sync(0xffffffffu, mx, 2));
            if (__any_sync(0xffffffffu, mx > m)) {
                const float n = fmaxf(m, mx);
                const float f = ex2((m - n) * CS), fo = __shfl_xor_sync(0xffffffffu, f, 4);
                const float f0 = h1 ? fo : f, f1 = h1 ? f : fo;
                m = n;
                ls[0] *= f0; ls[1] *= f1;
                #pragma unroll
                for (int i = 0; i < 4; i++) { o[i][0] *= f0; o[i][1] *= f1; o[i][2] *= f0; o[i][3] *= f1; }
            }
            const float mc = m * CS;
            uint32_t pb[4][2];
            #pragma unroll
            for (int kk = 0; kk < 4; kk++) {
                pb[kk][0] = pack_bf16(ex2(fmaf(x[kk].x, CS, -mc)), ex2(fmaf(x[kk].y, CS, -mc)));
                pb[kk][1] = pack_bf16(ex2(fmaf(x[kk].z, CS, -mc)), ex2(fmaf(x[kk].w, CS, -mc)));
                const uint32_t ones[4] = {0x3F803F80u, 0x3F803F80u, 0x3F803F80u, 0x3F803F80u};
                mma16816(ls, ones, pb[kk][0], pb[kk][1]);
            }
            mbar_wait(fullb + 8 * slot, ph);
            {
                const uint32_t vb = base + L::ring + slot * SLOT + warp * 8192;
                #pragma unroll
                for (int kk = 0; kk < 4; kk++)
                    #pragma unroll
                    for (int a4 = 0; a4 < 4; a4++) {
                        uint32_t a[4];
                        ldsm4t(a, vb + kk * 2048 + (offT ^ (a4 << 5)));
                        mma16816(o[a4], a, pb[kk][0], pb[kk][1]);
                    }
            }
            release();
            advance();
        }

        {
            const float Ls = h1 ? ls[1] : ls[0];
            const float inv = rcp(Ls);
            const uint32_t lse = (__float_as_uint(fmaf(m, CS, lg2(Ls))) & ~TM) | tg;
            float v[4];
            #pragma unroll
            for (int i = 0; i < 4; i++) {
                const float a = (t4 & 1) ? o[1][i] : o[0][i], b = (t4 & 1) ? o[3][i] : o[2][i];
                v[i] = (t4 & 2) ? b : a;
            }
            const float ka = h1 ? v[1] : v[0], kb = h1 ? v[3] : v[2];
            const float ra = __shfl_xor_sync(0xffffffffu, h1 ? v[0] : v[1], 4), rb = __shfl_xor_sync(0xffffffffu, h1 ? v[2] : v[3], 4);
            const uint32_t r0 = __float_as_uint((h1 ? ra : ka) * inv), r1 = __float_as_uint((h1 ? ka : ra) * inv);
            const uint32_t r2 = __float_as_uint((h1 ? rb : kb) * inv), r3 = __float_as_uint((h1 ? kb : rb) * inv);
            st_ll16(pubp + p * PP, __byte_perm(r0, r3, 0x3215), __byte_perm(r1, r3, 0x3216), __byte_perm(r2, r3, 0x3217), lse);
        }
        if (pi == 0) {
            if (tid == 0) flags[2] = 1;
            asm volatile("barrier.cluster.wait.acquire.aligned;" ::: "memory");
        }
    }

    if (pj) {
        if (j >= 120) {
            return;
        }
        uint32_t of[NWO][4][2];
        mbar_wait(wob + 8 * NWO + 8, 0);
        {
            const uint32_t oa = base + L::obs + (g & 1) * OBS + warp * 128 + t4 * 8;
            #pragma unroll
            for (int c = 0; c < NWO; c++)
                #pragma unroll
                for (int i = 0; i < 4; i++) lds64(of[c][i], oa + c * 512 + i * 32);
        }
        const uint32_t row = l7 + (lane >> 4) * 8;
        const uint32_t wa = base + L::ring + (NKV % S) * SLOT + warp * 2048 + row * 32 + ((((lane >> 3) & 1) ^ ((row >> 2) & 1)) << 4);
        const uint32_t fdst = mapa0(base + L::fb + ((j & 1) * 4 + warp) * 128 + g * 16), fbar = mapa0(wob + 8 * NWO + 16);
        float acc[4][4];
        #pragma unroll
        for (int i = 0; i < 4; i++) { acc[i][0] = 0.f; acc[i][1] = 0.f; acc[i][2] = 0.f; acc[i][3] = 0.f; }
        #pragma unroll
        for (int c = 0; c < NWO; c++) {
            mbar_wait(wob + 8 * c, 0);
            #pragma unroll
            for (int i = 0; i < 4; i++) {
                uint32_t a[4];
                ldsm4t(a, wa + c * 8192 + i * 512);
                mma16816(acc[i], a, of[c][i][0], of[c][i][1]);
            }
        }
        const float e0 = (acc[0][0] + acc[1][0]) + (acc[2][0] + acc[3][0]), e1 = (acc[0][1] + acc[1][1]) + (acc[2][1] + acc[3][1]);
        const float e2 = (acc[0][2] + acc[1][2]) + (acc[2][2] + acc[3][2]), e3 = (acc[0][3] + acc[1][3]) + (acc[2][3] + acc[3][3]);
        if (t4 == 0) st_async16(fdst, e0, e1, e2, e3, fbar);
        if (warp == 0 && !(j & 1)) {
            mbar_wait_cluster(wob + 8 * NWO + 16, 0);
            const float* fb = reinterpret_cast<const float*>(sm + L::fb) + (lane & 7) * 4 + ((lane >> 3) & 1) * 2 + (lane >> 4);
            const float v = ((fb[0] + fb[32]) + (fb[64] + fb[96])) + ((fb[128] + fb[160]) + (fb[192] + fb[224]));
            *fout = __float2bfloat16_rn(v);
        }
        return;
    }
    {
        uint32_t wf[4][7][4];
        uint32_t wa[7];
        {
            const uint32_t row = l7 + (lane >> 4) * 8, u = warp * 2 + ((lane >> 3) & 1);
            #pragma unroll
            for (int c = 0; c < 7; c++) wa[c] = base + L::ring + (NKV % S) * SLOT + row * 896 + c * 128 + ((u ^ ((c - row) & 7)) << 4);
        }
        auto waitk = [&](int ks) {
            #pragma unroll
            for (int b = ks * 16 / RBA; b < (ks * 16 + 16) / RBA; b++) mbar_wait(wob + 8 * b, 0);
        };
        auto ldw = [&](int ks) {
            #pragma unroll
            for (int c = 0; c < 7; c++) ldsm4t(wf[ks][c], wa[c] + ks * 14336);
        };
        #pragma unroll
        for (int ks = 0; ks < 3; ks++) { waitk(ks); ldw(ks); }
        bool l3 = false;
        {
            const long long t0 = clock64();
            while (!mbar_test(wob + 8 * NWO, 0)) {
                if (!l3 && mbar_test(wob + 8 * (NWO - 1), 0) && mbar_test(wob + 8 * (NWO - 2), 0)) { ldw(3); l3 = true; }
                else if (clock64() - t0 > SPIN_LIMIT) __trap();
            }
        }
        uint32_t of[4][2];
        const uint32_t oa = base + L::os + (g & 1) * OSS + t4 * 8;
        #pragma unroll
        for (int ks = 0; ks < 4; ks++) lds64(of[ks], oa + ks * 32);
        float acc[7][4];
        #pragma unroll
        for (int c = 0; c < 7; c++) { acc[c][0] = 0.f; acc[c][1] = 0.f; acc[c][2] = 0.f; acc[c][3] = 0.f; }
        #pragma unroll
        for (int ks = 0; ks < 3; ks++)
            #pragma unroll
            for (int c = 0; c < 7; c++) mma16816(acc[c], wf[ks][c], of[ks][0], of[ks][1]);
        if (!l3) { waitk(3); ldw(3); }
        #pragma unroll
        for (int c = 0; c < 7; c++) mma16816(acc[c], wf[3][c], of[3][0], of[3][1]);
        float e[4], f[4];
        #pragma unroll
        for (int i = 0; i < 4; i++) {
            const float x = (t4 & 1) ? acc[1][i] : acc[0][i], y = (t4 & 1) ? acc[3][i] : acc[2][i];
            e[i] = (t4 & 2) ? y : x;
            const float z = (t4 & 1) ? acc[5][i] : acc[4][i];
            f[i] = (t4 & 2) ? acc[6][i] : z;
        }
        st_ll16(pubo, __float_as_uint(e[0]), __float_as_uint(e[1]), __float_as_uint(e[2]), (__float_as_uint(e[3]) & ~TM) | tg);
        if (t4 < 3)
            st_ll16(pubo + 32 * OB, __float_as_uint(f[0]), __float_as_uint(f[1]), __float_as_uint(f[2]), (__float_as_uint(f[3]) & ~TM) | tg);
    }

    if (j < 56) {
        uint4 va[2];
        #pragma unroll
        for (int i = 0; i < 2; i++) va[i] = ld_ll16(fsrc + i * 32);
        for (uint32_t it = 0;; it++) {
            const uint32_t bad = ((va[0].w ^ tg) | (va[1].w ^ tg)) & TM;
            if (__all_sync(0xffffffffu, bad == 0)) break;
            #pragma unroll
            for (int i = 0; i < 2; i++)
                if ((va[i].w ^ tg) & TM) va[i] = ld_ll16(fsrc + i * 32);
            if (it > POLL_LIMIT) __trap();
        }
        const float s0 = __uint_as_float(va[0].x) + __uint_as_float(va[1].x), s1 = __uint_as_float(va[0].y) + __uint_as_float(va[1].y);
        const float s2 = __uint_as_float(va[0].z) + __uint_as_float(va[1].z);
        const float s3 = __uint_as_float(va[0].w & ~TM) + __uint_as_float(va[1].w & ~TM);
        const bool h16 = lane & 16, h8 = lane & 8;
        const float a = (h16 ? s2 : s0) + __shfl_xor_sync(0xffffffffu, h16 ? s0 : s2, 16);
        const float b = (h16 ? s3 : s1) + __shfl_xor_sync(0xffffffffu, h16 ? s1 : s3, 16);
        const float c = (h8 ? b : a) + __shfl_xor_sync(0xffffffffu, h8 ? a : b, 8);
        float* fr = reinterpret_cast<float*>(sm + L::red);
        fr[((lane >> 3) * 4 + (lane & 3)) * 12 + warp * 2 + ((lane >> 2) & 1)] = c;
        cons_sync();
        if (tid < 16) {
            const float4 x = reinterpret_cast<const float4*>(fr)[tid * 3], y = reinterpret_cast<const float4*>(fr)[tid * 3 + 1];
            const float v = ((x.x + x.y) + (x.z + x.w)) + ((y.x + y.y) + (y.z + y.w));
            *fout = __float2bfloat16_rn(v);
            if (j == 0 && tid == 0)
                asm volatile("st.relaxed.gpu.global.u32 [%0], %1;" ::"l"(epoch), "r"(tag) : "memory");
        }
    }
}

typedef CUresult (*EncodeFn)(CUtensorMap*, CUtensorMapDataType, cuuint32_t, void*, const cuuint64_t*, const cuuint64_t*,
                             const cuuint32_t*, const cuuint32_t*, CUtensorMapInterleave, CUtensorMapSwizzle,
                             CUtensorMapL2promotion, CUtensorMapFloatOOBfill);

inline CUtensorMap make_map(EncodeFn enc, const void* ptr, int rank, const cuuint64_t* dims, const cuuint64_t* strides, const cuuint32_t* box,
                            CUtensorMapSwizzle sw = CU_TENSOR_MAP_SWIZZLE_128B) {
    CUtensorMap m;
    const cuuint32_t es[3] = {1, 1, 1};
    enc(&m, CU_TENSOR_MAP_DATA_TYPE_BFLOAT16, rank, const_cast<void*>(ptr), dims, strides, box, es,
        CU_TENSOR_MAP_INTERLEAVE_NONE, sw, CU_TENSOR_MAP_L2_PROMOTION_NONE, CU_TENSOR_MAP_FLOAT_OOB_FILL_NONE);
    return m;
}

}

static void launch_pairs(void* const* d_in, void* d_out) {
    using namespace dk2;
    void* fn = nullptr;
    cudaDriverEntryPointQueryResult qr;
    cudaGetDriverEntryPoint("cuTensorMapEncodeTiled", &fn, cudaEnableDefault, &qr);
    EncodeFn enc = (EncodeFn)fn;

    const cuuint64_t kvd[3] = {64, 131072, 4}, kvs[2] = {512, 128};
    const cuuint32_t kvb[3] = {64, 64, 4};
    const cuuint64_t wqd[2] = {4096, 448}, wqs[1] = {8192};
    const cuuint32_t wqb[2] = {64, 224};
    const cuuint64_t wod[3] = {64, 7, 4096}, wos[2] = {128, 896};
    const cuuint32_t wob[3] = {64, 7, RBA};
    const CUtensorMap kA = make_map(enc, d_in[1], 3, kvd, kvs, kvb), vA = make_map(enc, d_in[2], 3, kvd, kvs, kvb);
    const CUtensorMap kB = make_map(enc, d_in[6], 3, kvd, kvs, kvb), vB = make_map(enc, d_in[7], 3, kvd, kvs, kvb);
    const CUtensorMap wqA = make_map(enc, d_in[3], 2, wqd, wqs, wqb), wqB = make_map(enc, d_in[8], 2, wqd, wqs, wqb);
    const cuuint64_t wcd[2] = {448, 4096}, wcs[1] = {896};
    const cuuint32_t wcb[2] = {16, RBB};
    const CUtensorMap woA = make_map(enc, d_in[4], 3, wod, wos, wob);
    const CUtensorMap woB = make_map(enc, d_in[9], 2, wcd, wcs, wcb, CU_TENSOR_MAP_SWIZZLE_32B);
    Params prm;
    prm.xA = (const __nv_bfloat16*)d_in[0];
    prm.xB = (const __nv_bfloat16*)d_in[5];
    prm.wqA = (const __nv_bfloat16*)d_in[3];
    prm.wqB = (const __nv_bfloat16*)d_in[8];
    prm.kB = (const __nv_bfloat16*)d_in[6];
    prm.vB = (const __nv_bfloat16*)d_in[7];
    prm.kA = (const __nv_bfloat16*)d_in[1];
    prm.vA = (const __nv_bfloat16*)d_in[2];
    prm.out = (__nv_bfloat16*)d_out;
    void* a = nullptr;
    cudaGetSymbolAddress(&a, g_epoch); prm.epoch = (unsigned*)a;
    cudaGetSymbolAddress(&a, g_q);     prm.q = (uint2*)a;
    cudaGetSymbolAddress(&a, g_part);  prm.part = (uint4*)a;
    cudaGetSymbolAddress(&a, g_out);   prm.outp = (uint4*)a;
    cudaGetSymbolAddress(&a, g_ob);    prm.ob = (uint2*)a;

    cudaFuncSetAttribute(decode_kernel, cudaFuncAttributeMaxDynamicSharedMemorySize, Smem::total);
    decode_kernel<<<NCTA, NTHREADS, Smem::total>>>(kA, vA, kB, vB, wqA, wqB, woA, woB, prm);
}

extern "C" void kernel_launch(void* const* d_in, const int* in_sizes, int n_in, void* d_out, int out_size) {
    (void)in_sizes; (void)n_in; (void)out_size;
    static int octets = -1;
    if (octets < 0) {
        cudaFuncSetAttribute(dk8::decode_kernel, cudaFuncAttributeMaxDynamicSharedMemorySize, dk8::Smem::total);
        cudaLaunchConfig_t cfg = {};
        cfg.gridDim = dim3(dk8::NCTA, 1, 1);
        cfg.blockDim = dim3(dk8::NTHREADS, 1, 1);
        cfg.dynamicSmemBytes = dk8::Smem::total;
        cudaLaunchAttribute at;
        at.id = cudaLaunchAttributeClusterDimension;
        at.val.clusterDim.x = 8; at.val.clusterDim.y = 1; at.val.clusterDim.z = 1;
        cfg.attrs = &at; cfg.numAttrs = 1;
        int n = 0;
        const cudaError_t e = cudaOccupancyMaxActiveClusters(&n, dk8::decode_kernel, &cfg);
        if (e != cudaSuccess) (void)cudaGetLastError();
        octets = (e == cudaSuccess && n * 8 >= dk8::NCTA) ? 1 : 0;
    }
    if (octets) launch_octets(d_in, d_out); else launch_pairs(d_in, d_out);
}
```
